```python
import torch

def _softmax(x, axis=-1):
    return torch.softmax(x, dim=axis)
def _gelu(x):
    return torch.nn.functional.gelu(x, approximate="tanh")
def _silu(x):
    return torch.nn.functional.silu(x)
def _sigmoid(x):
    return torch.sigmoid(x)
def _layernorm(x, axis=-1, eps=1e-5):
    m = x.mean(dim=axis, keepdim=True)
    v = x.var(dim=axis, keepdim=True, unbiased=False)
    return (x - m) / torch.sqrt(v + eps)
def _scatter_add(tgt, idx, src, axis=0):
    return tgt.clone().index_add_(axis, idx, src)
def _segment_sum(src, seg, n):
    out = torch.zeros((n,) + src.shape[1:], dtype=src.dtype)
    return out.index_add_(0, seg, src)
def _pad(x, pw):
    flat = tuple(v for pair in reversed(pw) for v in pair)
    return torch.nn.functional.pad(x, flat)

kernel_name = 'gated_mix__spectral_fnet__geglu_ffn__prompt'

def setup_inputs():

    _w = (lambda a: (lambda t: t.to(torch.bfloat16) if t.is_floating_point() else t)(torch.as_tensor(a)))
    def _A_setup():
        B, S, D = 1, 2048, 640
        ns = torch.arange(S)[:, None] * torch.arange(S)[None, :]
        nd = torch.arange(D)[:, None] * torch.arange(D)[None, :]
        Ws_re = torch.cos(-2.0 * torch.pi * ns / S).to(float)
        Ws_im = torch.sin(-2.0 * torch.pi * ns / S).to(float)
        Wd_re = torch.cos(-2.0 * torch.pi * nd / D).to(float)
        Wd_im = torch.sin(-2.0 * torch.pi * nd / D).to(float)
        return {
            "x": _w((lambda *s: torch.randn(*s, dtype=torch.bfloat16) * 0.05)(B, S, D)),
            "dft_seq_re": _w(Ws_re),
            "dft_seq_im": _w(Ws_im),
            "dft_hid_re": _w(Wd_re),
            "dft_hid_im": _w(Wd_im),
        }
    _A_in = _A_setup()

    def _B_setup():
        B, S, D, F = 1, 2048, 640, 1536
        return {
            "x": _w((lambda *s: torch.randn(*s, dtype=torch.bfloat16) * 0.05)(B, S, D)),
            "w_gate": _w((lambda *s: torch.randn(*s, dtype=torch.bfloat16) * 0.8)(D, F)),
            "w_up": _w((lambda *s: torch.randn(*s, dtype=torch.bfloat16) * 0.8)(D, F)),
            "w_down": _w((lambda *s: torch.randn(*s, dtype=torch.bfloat16) * 0.8)(F, D)),
        }
    _B_in = _B_setup()

    return {
        "A_x": _A_in["x"],
        "A_dft_seq_re": _A_in["dft_seq_re"],
        "A_dft_seq_im": _A_in["dft_seq_im"],
        "A_dft_hid_re": _A_in["dft_hid_re"],
        "A_dft_hid_im": _A_in["dft_hid_im"],
        "B_x": _B_in["x"],
        "B_w_gate": _B_in["w_gate"],
        "B_w_up": _B_in["w_up"],
        "B_w_down": _B_in["w_down"],
        "gate_w": _w((lambda *s: torch.randn(*s, dtype=torch.bfloat16) * 0.05)(640) * 16.0),
    }

def reference(A_x, A_dft_seq_re, A_dft_seq_im, A_dft_hid_re, A_dft_hid_im, B_x, B_w_gate, B_w_up, B_w_down, gate_w):
    def _A_ref(x, dft_seq_re, dft_seq_im, dft_hid_re, dft_hid_im):
        a = torch.einsum("bsd,ed->bse", x, dft_hid_re)
        b = torch.einsum("bsd,ed->bse", x, dft_hid_im)
        y = torch.einsum("ts,bse->bte", dft_seq_re, a) - torch.einsum("ts,bse->bte", dft_seq_im, b)
        return y

    def _B_ref(x, w_gate, w_up, w_down):
        return (_gelu(x @ w_gate) * (x @ w_up)) @ w_down

    x = A_x
    g = _sigmoid((x * gate_w).sum(-1, keepdims=True))
    a = _A_ref(x, A_dft_seq_re, A_dft_seq_im, A_dft_hid_re, A_dft_hid_im)
    b = _B_ref(x, B_w_gate, B_w_up, B_w_down)
    return g * a + (1 - g) * b
```

```cpp
#include <cuda_runtime.h>
#include <cuda_bf16.h>
#include <cuda.h>
#include <stdint.h>

typedef __nv_bfloat16 bf16;

constexpr int S_ = 2048, D_ = 640, F_ = 1536;
constexpr int NCTA = 132;

__device__ bf16 g_abT[2 * D_ * S_];
__device__ bf16 g_H[S_ * F_];
__device__ float4 g_xch[128 * 20 * 128];
__device__ unsigned g_cnt[64 * 32];
#define PROF_T(idx) do { } while (0)

struct Maps {
    CUtensorMap x, wdre, wdim, wg, wu, wsre, wsim, abT_ld, abT_st, h, wdown, out;
};

constexpr int R1_STAGE = 49152, R1_N = 4;
constexpr int R2_STAGE = 36864, R2_N = 5;
constexpr int STG_OFF = 196608, STG_SZ = 16384;
constexpr int RECV_OFF = 184320;
constexpr int BAR_OFF = 229376;
constexpr int B_FULL1 = BAR_OFF, B_EMPTY1 = BAR_OFF + 32, B_FULL2 = BAR_OFF + 64, B_EMPTY2 = BAR_OFF + 104;
constexpr int B_STGF = BAR_OFF + 144, B_STGE = BAR_OFF + 160, B_GRDY = BAR_OFF + 176;
constexpr int G_OFF = BAR_OFF + 256, EPOCH_OFF = BAR_OFF + 768;
constexpr int SMEM_BYTES = BAR_OFF + 1024;

__device__ __forceinline__ void trap_if(uint32_t cond) { asm volatile("{\n.reg .pred p;\nsetp.ne.u32 p, %0, 0;\n@p trap;\n}" ::"r"(cond)); }
__device__ __forceinline__ uint32_t smem_u32(const void* p) { return (uint32_t)__cvta_generic_to_shared(p); }
__device__ __forceinline__ void mbar_init(uint32_t bar, int count) { asm volatile("mbarrier.init.shared::cta.b64 [%0], %1;" ::"r"(bar), "r"(count)); }
__device__ __forceinline__ void mbar_expect_tx(uint32_t bar, uint32_t bytes) {
    asm volatile("mbarrier.arrive.expect_tx.shared::cta.b64 _, [%0], %1;" ::"r"(bar), "r"(bytes) : "memory");
}
__device__ __forceinline__ void mbar_arrive(uint32_t bar) { asm volatile("mbarrier.arrive.shared::cta.b64 _, [%0];" ::"r"(bar) : "memory"); }
__device__ __forceinline__ void mbar_arrive_cluster(uint32_t bar, uint32_t cta) {
    asm volatile("{\n.reg .b32 ra;\nmapa.shared::cluster.u32 ra, %0, %1;\nmbarrier.arrive.shared::cluster.b64 _, [ra];\n}" ::"r"(bar), "r"(cta) : "memory");
}
__device__ __forceinline__ void mbar_wait(uint32_t bar, uint32_t parity) {
    asm volatile(
        "{\n.reg .pred p;\n.reg .u32 n;\nmov.u32 n, 0;\nLAB_WAIT:\n"
        "mbarrier.try_wait.parity.shared::cta.b64 p, [%0], %1;\n@p bra DONE;\n"
        "add.u32 n, n, 1;\nsetp.lt.u32 p, n, 1048576;\n@p bra LAB_WAIT;\ntrap;\nDONE:\n}" ::"r"(bar), "r"(parity) : "memory");
}
__device__ __forceinline__ void flag_wait(const unsigned* p, unsigned target) {
    asm volatile(
        "{\n.reg .pred p;\n.reg .u32 n, v;\n.reg .s32 d;\nmov.u32 n, 0;\nLAB_WAIT:\n"
        "ld.acquire.gpu.global.u32 v, [%0];\nsub.s32 d, v, %1;\nsetp.ge.s32 p, d, 0;\n@p bra DONE;\n"
        "add.u32 n, n, 1;\nsetp.lt.u32 p, n, 4194304;\n@p bra LAB_WAIT;\ntrap;\nDONE:\n}" ::"l"(p), "r"(target) : "memory");
    asm volatile("fence.proxy.async;" ::: "memory");
}
__device__ __forceinline__ unsigned ld_relaxed(const unsigned* p) {
    unsigned v;
    asm volatile("ld.relaxed.gpu.global.u32 %0, [%1];" : "=r"(v) : "l"(p) : "memory");
    return v;
}
__device__ __forceinline__ void tma_2d(uint32_t dst, const CUtensorMap* tm, int c0, int c1, uint32_t bar) {
    asm volatile("cp.async.bulk.tensor.2d.shared::cluster.global.mbarrier::complete_tx::bytes [%0], [%1, {%3, %4}], [%2];" ::"r"(dst), "l"(tm), "r"(bar), "r"(c0), "r"(c1) : "memory");
}
__device__ __forceinline__ void tma_2d_mc(uint32_t dst, const CUtensorMap* tm, int c0, int c1, uint32_t bar) {
    asm volatile("cp.async.bulk.tensor.2d.shared::cluster.global.mbarrier::complete_tx::bytes.multicast::cluster [%0], [%1, {%3, %4}], [%2], %5;" ::"r"(dst), "l"(tm), "r"(bar), "r"(c0), "r"(c1), "h"((uint16_t)3) : "memory");
}
__device__ __forceinline__ void tma_3d_mc(uint32_t dst, const CUtensorMap* tm, int c0, int c1, int c2, uint32_t bar) {
    asm volatile("cp.async.bulk.tensor.3d.shared::cluster.global.mbarrier::complete_tx::bytes.multicast::cluster [%0], [%1, {%3, %4, %5}], [%2], %6;" ::"r"(dst), "l"(tm), "r"(bar), "r"(c0), "r"(c1), "r"(c2), "h"((uint16_t)3) : "memory");
}
__device__ __forceinline__ void tma_store_2d(const CUtensorMap* tm, uint32_t src, int c0, int c1) {
    asm volatile("cp.async.bulk.tensor.2d.global.shared::cta.bulk_group [%0, {%2, %3}], [%1];" ::"l"(tm), "r"(src), "r"(c0), "r"(c1) : "memory");
}
__device__ __forceinline__ void tma_store_3d(const CUtensorMap* tm, uint32_t src, int c0, int c1, int c2) {
    asm volatile("cp.async.bulk.tensor.3d.global.shared::cta.bulk_group [%0, {%2, %3, %4}], [%1];" ::"l"(tm), "r"(src), "r"(c0), "r"(c1), "r"(c2) : "memory");
}
__device__ __forceinline__ void tma_prefetch_2d(const CUtensorMap* tm, int c0, int c1) {
    asm volatile("cp.async.bulk.prefetch.tensor.2d.L2.global [%0, {%1, %2}];" ::"l"(tm), "r"(c0), "r"(c1) : "memory");
}
__device__ __forceinline__ void bulk_prefetch(const void* p, uint32_t bytes) {
    asm volatile("cp.async.bulk.prefetch.L2.global [%0], %1;" ::"l"(p), "r"(bytes) : "memory");
}
__device__ __forceinline__ void prefetch_map(const CUtensorMap* tm) { asm volatile("prefetch.tensormap [%0];" ::"l"(tm) : "memory"); }
__device__ __forceinline__ void bulk_commit() { asm volatile("cp.async.bulk.commit_group;" ::: "memory"); }
__device__ __forceinline__ void bulk_wait_read0() { asm volatile("cp.async.bulk.wait_group.read 0;" ::: "memory"); }
__device__ __forceinline__ void bulk_wait0() { asm volatile("cp.async.bulk.wait_group 0;" ::: "memory"); }
__device__ __forceinline__ void fence_async_smem() { asm volatile("fence.proxy.async.shared::cta;" ::: "memory"); }
__device__ __forceinline__ void wgmma_fence() { asm volatile("wgmma.fence.sync.aligned;" ::: "memory"); }
__device__ __forceinline__ void wgmma_commit() { asm volatile("wgmma.commit_group.sync.aligned;" ::: "memory"); }
template <int N> __device__ __forceinline__ void wgmma_wait() { asm volatile("wgmma.wait_group.sync.aligned %0;" ::"n"(N) : "memory"); }
__device__ __forceinline__ void cluster_arrive_relaxed() { asm volatile("barrier.cluster.arrive.relaxed.aligned;" ::: "memory"); }
__device__ __forceinline__ void cluster_wait() { asm volatile("barrier.cluster.wait.acquire.aligned;" ::: "memory"); }
__device__ __forceinline__ void bar_sync(int id, int n) { asm volatile("bar.sync %0, %1;" ::"r"(id), "r"(n) : "memory"); }
__device__ __forceinline__ void bar_arrive(int id, int n) { asm volatile("bar.arrive %0, %1;" ::"r"(id), "r"(n) : "memory"); }
__device__ __forceinline__ constexpr uint64_t desc_hi(uint32_t lbo, uint32_t sbo, uint64_t swz) {
    return ((uint64_t)(lbo >> 4) << 16) | ((uint64_t)(sbo >> 4) << 32) | (swz << 62);
}
__device__ __forceinline__ uint64_t mk_desc(uint64_t hi, uint32_t addr) { return hi | (uint64_t)((addr & 0x3FFFF) >> 4); }
__device__ __forceinline__ void stmatrix_x4(uint32_t addr, uint32_t r0, uint32_t r1, uint32_t r2, uint32_t r3) {
    asm volatile("stmatrix.sync.aligned.m8n8.x4.shared.b16 [%0], {%1, %2, %3, %4};" ::"r"(addr), "r"(r0), "r"(r1), "r"(r2), "r"(r3) : "memory");
}
__device__ __forceinline__ uint32_t pack_bf16(float lo, float hi) {
    uint32_t r;
    asm("cvt.rn.bf16x2.f32 %0, %1, %2;" : "=r"(r) : "f"(hi), "f"(lo));
    return r;
}
__device__ __forceinline__ float bf_lo(uint32_t v) { return __uint_as_float(v << 16); }
__device__ __forceinline__ float bf_hi(uint32_t v) { return __uint_as_float(v & 0xffff0000u); }
__device__ __forceinline__ float geglu(float x, float u) {
    const float c0 = -2.0f * 0.7978845608028654f * 1.4426950408889634f;
    const float c1 = c0 * 0.044715f;
    float t = fmaf(x * x, c1, c0) * x, e, r;
    asm("ex2.approx.ftz.f32 %0, %1;" : "=f"(e) : "f"(t));
    asm("rcp.approx.ftz.f32 %0, %1;" : "=f"(r) : "f"(1.0f + e));
    return (x * u) * r;
}
__device__ __forceinline__ uint32_t geglu2(uint32_t g, uint32_t u) { return pack_bf16(geglu(bf_lo(g), bf_lo(u)), geglu(bf_hi(g), bf_hi(u))); }

template <int TB>
__device__ __forceinline__ void wgmma_n256(float (&d)[128], uint64_t da, uint64_t db, int scale_d) {
    asm volatile(
        "{\n.reg .pred p;\nsetp.ne.b32 p, %130, 0;\n"
        "wgmma.mma_async.sync.aligned.m64n256k16.f32.bf16.bf16 {"
        "%0, %1, %2, %3, %4, %5, %6, %7, %8, %9, %10, %11, %12, %13, %14, %15, %16, %17, %18, %19, %20, %21, %22, %23, %24, %25, %26, %27, %28, %29, %30, %31, "
        "%32, %33, %34, %35, %36, %37, %38, %39, %40, %41, %42, %43, %44, %45, %46, %47, %48, %49, %50, %51, %52, %53, %54, %55, %56, %57, %58, %59, %60, %61, "
        "%62, %63, %64, %65, %66, %67, %68, %69, %70, %71, %72, %73, %74, %75, %76, %77, %78, %79, %80, %81, %82, %83, %84, %85, %86, %87, %88, %89, %90, %91, "
        "%92, %93, %94, %95, %96, %97, %98, %99, %100, %101, %102, %103, %104, %105, %106, %107, %108, %109, %110, %111, %112, %113, %114, %115, %116, %117, "
        "%118, %119, %120, %121, %122, %123, %124, %125, %126, %127"
        "}, %128, %129, p, 1, 1, 0, %131;\n}\n"
        : "+f"(d[0]), "+f"(d[1]), "+f"(d[2]), "+f"(d[3]), "+f"(d[4]), "+f"(d[5]), "+f"(d[6]), "+f"(d[7]), "+f"(d[8]), "+f"(d[9]), "+f"(d[10]), "+f"(d[11]),
          "+f"(d[12]), "+f"(d[13]), "+f"(d[14]), "+f"(d[15]), "+f"(d[16]), "+f"(d[17]), "+f"(d[18]), "+f"(d[19]), "+f"(d[20]), "+f"(d[21]), "+f"(d[22]),
          "+f"(d[23]), "+f"(d[24]), "+f"(d[25]), "+f"(d[26]), "+f"(d[27]), "+f"(d[28]), "+f"(d[29]), "+f"(d[30]), "+f"(d[31]), "+f"(d[32]), "+f"(d[33]),
          "+f"(d[34]), "+f"(d[35]), "+f"(d[36]), "+f"(d[37]), "+f"(d[38]), "+f"(d[39]), "+f"(d[40]), "+f"(d[41]), "+f"(d[42]), "+f"(d[43]), "+f"(d[44]),
          "+f"(d[45]), "+f"(d[46]), "+f"(d[47]), "+f"(d[48]), "+f"(d[49]), "+f"(d[50]), "+f"(d[51]), "+f"(d[52]), "+f"(d[53]), "+f"(d[54]), "+f"(d[55]),
          "+f"(d[56]), "+f"(d[57]), "+f"(d[58]), "+f"(d[59]), "+f"(d[60]), "+f"(d[61]), "+f"(d[62]), "+f"(d[63]), "+f"(d[64]), "+f"(d[65]), "+f"(d[66]),
          "+f"(d[67]), "+f"(d[68]), "+f"(d[69]), "+f"(d[70]), "+f"(d[71]), "+f"(d[72]), "+f"(d[73]), "+f"(d[74]), "+f"(d[75]), "+f"(d[76]), "+f"(d[77]),
          "+f"(d[78]), "+f"(d[79]), "+f"(d[80]), "+f"(d[81]), "+f"(d[82]), "+f"(d[83]), "+f"(d[84]), "+f"(d[85]), "+f"(d[86]), "+f"(d[87]), "+f"(d[88]),
          "+f"(d[89]), "+f"(d[90]), "+f"(d[91]), "+f"(d[92]), "+f"(d[93]), "+f"(d[94]), "+f"(d[95]), "+f"(d[96]), "+f"(d[97]), "+f"(d[98]), "+f"(d[99]),
          "+f"(d[100]), "+f"(d[101]), "+f"(d[102]), "+f"(d[103]), "+f"(d[104]), "+f"(d[105]), "+f"(d[106]), "+f"(d[107]), "+f"(d[108]), "+f"(d[109]),
          "+f"(d[110]), "+f"(d[111]), "+f"(d[112]), "+f"(d[113]), "+f"(d[114]), "+f"(d[115]), "+f"(d[116]), "+f"(d[117]), "+f"(d[118]), "+f"(d[119]),
          "+f"(d[120]), "+f"(d[121]), "+f"(d[122]), "+f"(d[123]), "+f"(d[124]), "+f"(d[125]), "+f"(d[126]), "+f"(d[127])
        : "l"(da), "l"(db), "r"(scale_d), "n"(TB));
}
template <int TB>
__device__ __forceinline__ void wgmma_n160(float (&d)[80], uint64_t da, uint64_t db, int scale_d) {
    asm volatile(
        "{\n.reg .pred p;\nsetp.ne.b32 p, %82, 0;\n"
        "wgmma.mma_async.sync.aligned.m64n160k16.f32.bf16.bf16 {"
        "%0, %1, %2, %3, %4, %5, %6, %7, %8, %9, %10, %11, %12, %13, %14, %15, %16, %17, %18, %19, %20, %21, %22, %23, %24, %25, %26, %27, %28, %29, %30, %31, "
        "%32, %33, %34, %35, %36, %37, %38, %39, %40, %41, %42, %43, %44, %45, %46, %47, %48, %49, %50, %51, %52, %53, %54, %55, %56, %57, %58, %59, %60, %61, "
        "%62, %63, %64, %65, %66, %67, %68, %69, %70, %71, %72, %73, %74, %75, %76, %77, %78, %79"
        "}, %80, %81, p, 1, 1, 0, %83;\n}\n"
        : "+f"(d[0]), "+f"(d[1]), "+f"(d[2]), "+f"(d[3]), "+f"(d[4]), "+f"(d[5]), "+f"(d[6]), "+f"(d[7]), "+f"(d[8]), "+f"(d[9]), "+f"(d[10]), "+f"(d[11]),
          "+f"(d[12]), "+f"(d[13]), "+f"(d[14]), "+f"(d[15]), "+f"(d[16]), "+f"(d[17]), "+f"(d[18]), "+f"(d[19]), "+f"(d[20]), "+f"(d[21]), "+f"(d[22]),
          "+f"(d[23]), "+f"(d[24]), "+f"(d[25]), "+f"(d[26]), "+f"(d[27]), "+f"(d[28]), "+f"(d[29]), "+f"(d[30]), "+f"(d[31]), "+f"(d[32]), "+f"(d[33]),
          "+f"(d[34]), "+f"(d[35]), "+f"(d[36]), "+f"(d[37]), "+f"(d[38]), "+f"(d[39]), "+f"(d[40]), "+f"(d[41]), "+f"(d[42]), "+f"(d[43]), "+f"(d[44]),
          "+f"(d[45]), "+f"(d[46]), "+f"(d[47]), "+f"(d[48]), "+f"(d[49]), "+f"(d[50]), "+f"(d[51]), "+f"(d[52]), "+f"(d[53]), "+f"(d[54]), "+f"(d[55]),
          "+f"(d[56]), "+f"(d[57]), "+f"(d[58]), "+f"(d[59]), "+f"(d[60]), "+f"(d[61]), "+f"(d[62]), "+f"(d[63]), "+f"(d[64]), "+f"(d[65]), "+f"(d[66]),
          "+f"(d[67]), "+f"(d[68]), "+f"(d[69]), "+f"(d[70]), "+f"(d[71]), "+f"(d[72]), "+f"(d[73]), "+f"(d[74]), "+f"(d[75]), "+f"(d[76]), "+f"(d[77]),
          "+f"(d[78]), "+f"(d[79])
        : "l"(da), "l"(db), "r"(scale_d), "n"(TB));
}

constexpr uint64_t DH_K128 = desc_hi(16, 1024, 1);
constexpr uint64_t DH_N128 = desc_hi(8192, 1024, 1);
constexpr uint64_t DH_N64 = desc_hi(2048, 512, 2);

struct Ctx {
    uint32_t sb;
    uint32_t a_off;
    uint32_t st_addr;
    uint32_t st_row7;
    uint32_t st_hi;
    uint32_t lane;
    int it1;
    int q;
};

__device__ __forceinline__ void release(uint32_t bar, uint32_t lane) {
    if (lane < 2) mbar_arrive_cluster(bar, lane);
}

template <int TB>
__device__ __forceinline__ void mma_s1(float (&acc)[128], const Ctx& c, int s, bool first) {
    const uint32_t sa = c.sb + s * R1_STAGE + c.a_off, sbb = c.sb + s * R1_STAGE + 16384;
    wgmma_fence();
#pragma unroll
    for (int k = 0; k < 4; k++) {
        uint64_t da = mk_desc(DH_K128, sa + k * 32);
        uint64_t db = TB ? mk_desc(DH_N128, sbb + k * 2048) : mk_desc(DH_K128, sbb + k * 32);
        wgmma_n256<TB>(acc, da, db, (k == 0 && first) ? 0 : 1);
    }
    wgmma_commit();
}
template <int TB>
__device__ __forceinline__ void mma_s2(float (&acc)[80], const Ctx& c, int s, bool first) {
    const uint32_t sa = c.sb + s * R2_STAGE + c.a_off, sbb = c.sb + s * R2_STAGE + 16384;
    wgmma_fence();
#pragma unroll
    for (int k = 0; k < 4; k++) {
        uint64_t da = mk_desc(DH_K128, sa + k * 32);
        uint64_t db = TB ? mk_desc(DH_N64, sbb + (k >> 1) * 10240 + (k & 1) * 1024) : mk_desc(DH_K128, sbb + k * 32);
        wgmma_n160<TB>(acc, da, db, (k == 0 && first) ? 0 : 1);
    }
    wgmma_commit();
}

__device__ __forceinline__ void stg_acquire(const Ctx& c) { mbar_wait(c.sb + B_STGE + 8 * (c.q & 1), ((c.q >> 1) & 1) ^ 1); }
__device__ __forceinline__ void stg_publish(Ctx& c) {
    fence_async_smem();
    __syncwarp();
    if (c.lane == 0) mbar_arrive(c.sb + B_STGF + 8 * (c.q & 1));
    c.q++;
}
__device__ __forceinline__ void stg_store(const Ctx& c, int p, uint32_t r0, uint32_t r1, uint32_t r2, uint32_t r3) {
    uint32_t addr = c.st_addr + (c.q & 1) * STG_SZ + (((2 * p + c.st_hi) ^ c.st_row7) << 4);
    stmatrix_x4(addr, r0, r1, r2, r3);
}
template <int I>
__device__ __forceinline__ void epi_h(uint32_t (&pk)[64], Ctx& c) {
    if (I == 0 || I == 4) stg_acquire(c);
#pragma unroll
    for (int j = 0; j < 4; j++) asm volatile("" : "+r"(pk[4 * I + j]), "+r"(pk[32 + 4 * I + j]));
    uint32_t r0 = geglu2(pk[4 * I + 0], pk[32 + 4 * I + 0]);
    uint32_t r1 = geglu2(pk[4 * I + 1], pk[32 + 4 * I + 1]);
    uint32_t r2 = geglu2(pk[4 * I + 2], pk[32 + 4 * I + 2]);
    uint32_t r3 = geglu2(pk[4 * I + 3], pk[32 + 4 * I + 3]);
    stg_store(c, I & 3, r0, r1, r2, r3);
    if (I == 3 || I == 7) stg_publish(c);
}
template <int C>
__device__ __forceinline__ void epi_ab(uint32_t (&pk)[64], Ctx& c) {
    stg_acquire(c);
#pragma unroll
    for (int p = 0; p < 4; p++) stg_store(c, p, pk[16 * C + 4 * p], pk[16 * C + 4 * p + 1], pk[16 * C + 4 * p + 2], pk[16 * C + 4 * p + 3]);
    stg_publish(c);
}
template <int I>
__device__ __forceinline__ void epi_step(uint32_t (&pk)[64], Ctx& c, bool prev_ab) {
    if (prev_ab) {
        if (I == 0) { epi_ab<0>(pk, c); epi_ab<1>(pk, c); }
        if (I == 1) { epi_ab<2>(pk, c); epi_ab<3>(pk, c); }
    } else {
        if (I < 8) epi_h<(I < 8 ? I : 0)>(pk, c);
    }
}
__device__ __forceinline__ void finish_s1(float (&acc)[128], uint32_t (&pk)[64], Ctx& c) {
    wgmma_wait<0>();
    release(c.sb + B_EMPTY1 + 8 * ((c.it1 - 1) & 3), c.lane);
#pragma unroll
    for (int i = 0; i < 128; i++) asm volatile("" : "+f"(acc[i])::"memory");
#pragma unroll
    for (int i = 0; i < 64; i++) pk[i] = pack_bf16(acc[2 * i], acc[2 * i + 1]);
}
template <int TB>
__device__ __forceinline__ void tile_plain(float (&acc)[128], Ctx& c) {
#pragma unroll 1
    for (int kb = 0; kb < 10; kb++) {
        const int s = c.it1 & 3;
        mbar_wait(c.sb + B_FULL1 + 8 * s, (c.it1 >> 2) & 1);
        mma_s1<TB>(acc, c, s, kb == 0);
        wgmma_wait<1>();
        if (kb > 0) release(c.sb + B_EMPTY1 + 8 * ((s - 1) & 3), c.lane);
        c.it1++;
    }
}
template <int I>
__device__ __forceinline__ void s1_epi_iter(float (&acc)[128], uint32_t (&pk)[64], Ctx& c, bool prev_ab) {
    const int s = c.it1 & 3;
    mbar_wait(c.sb + B_FULL1 + 8 * s, (c.it1 >> 2) & 1);
    mma_s1<1>(acc, c, s, I == 0);
    wgmma_wait<1>();
    if (I > 0) release(c.sb + B_EMPTY1 + 8 * ((s - 1) & 3), c.lane);
    c.it1++;
    epi_step<I>(pk, c, prev_ab);
}
template <int I>
__device__ __forceinline__ void s2_epi_iter(float (&acc)[80], uint32_t (&pk)[64], Ctx& c) {
    constexpr int s = I % R2_N;
    mbar_wait(c.sb + B_FULL2 + 8 * s, (I / R2_N) & 1);
    mma_s2<0>(acc, c, s, I == 0);
    wgmma_wait<1>();
    if (I > 0) release(c.sb + B_EMPTY2 + 8 * ((I + R2_N - 1) % R2_N), c.lane);
    epi_h<I>(pk, c);
}

__global__ void __cluster_dims__(2, 1, 1) __launch_bounds__(384, 1)
fused_kernel(const __grid_constant__ Maps maps, const bf16* __restrict__ x, const bf16* __restrict__ gw, const bf16* __restrict__ wdown) {
    extern __shared__ __align__(1024) uint8_t smem_raw[];
    const uint32_t sb = smem_u32(smem_raw);
    const int warp = __shfl_sync(0xffffffffu, threadIdx.x >> 5, 0);
    const uint32_t lane = threadIdx.x & 31;
    const int cl = blockIdx.x >> 1, rank = blockIdx.x & 1;
    const bool is_main = cl < 64;
    const int nrounds = is_main ? 2 : 4;
    const bool first_ab = cl < 40;
    const int m2 = 2 * (cl & 7) + rank, nb = (cl >> 3) & 3, kh = (cl >> 5) & 1;

    if (threadIdx.x == 0) {
        trap_if(sb & 1023);
        for (int s = 0; s < R1_N; s++) { mbar_init(sb + B_FULL1 + 8 * s, 1); mbar_init(sb + B_EMPTY1 + 8 * s, 16); }
        for (int s = 0; s < R2_N; s++) { mbar_init(sb + B_FULL2 + 8 * s, 1); mbar_init(sb + B_EMPTY2 + 8 * s, 16); }
        for (int s = 0; s < 2; s++) { mbar_init(sb + B_STGF + 8 * s, 8); mbar_init(sb + B_STGE + 8 * s, 1); }
        mbar_init(sb + B_GRDY, 2);
        asm volatile("fence.mbarrier_init.release.cluster;" ::: "memory");
    }
    if (warp == 9 && lane < 12) prefetch_map(&maps.x + lane);
    __syncthreads();
    cluster_arrive_relaxed();
    cluster_wait();

    auto h_tile = [&](int r, int& m, int& ct) {
        if (!is_main) { m = 2 * ((cl - 64) * 4 + r) + rank; ct = 11; }
        else if (r == 0) { m = 2 * ((cl - 40) & 7) + rank; ct = (cl - 40) >> 3; }
        else { m = m2; ct = 3 + (cl >> 3); }
    };
    const int ab_e = 2 * (cl % 5) + rank, ab_s = cl / 5;

    if (warp >= 8) {
        asm volatile("setmaxnreg.dec.sync.aligned.u32 40;");
        if (warp == 8) {
            if (lane == 0) {
                const unsigned epoch1 = ld_relaxed(&g_cnt[0]) / NCTA + 1;
                int it = 0;
                for (int r = 0; r < nrounds; r++) {
                    const bool ab = first_ab && r == 0;
                    int m, ct;
                    h_tile(r, m, ct);
                    const CUtensorMap* ma = ab ? (ab_e < 5 ? &maps.wdre : &maps.wdim) : &maps.x;
                    const int arow = ab ? (ab_e % 5) * 128 : m * 128;
                    const CUtensorMap* mw = rank == 0 ? &maps.wg : &maps.wu;
                    for (int kb = 0; kb < 10; kb++, it++) {
                        const int s = it & 3;
                        const uint32_t full = sb + B_FULL1 + 8 * s, dst = sb + s * R1_STAGE;
                        mbar_wait(sb + B_EMPTY1 + 8 * s, ((it >> 2) & 1) ^ 1);
                        mbar_expect_tx(full, R1_STAGE);
                        tma_2d(dst, ma, kb * 64, arow, full);
                        if (ab) tma_2d_mc(dst + 16384 + rank * 16384, &maps.x, kb * 64, ab_s * 256 + rank * 128, full);
                        else tma_3d_mc(dst + 16384 + rank * 16384, mw, 0, kb * 64, ct * 2, full);
                    }
                }
                if (is_main) {
                    PROF_T(32);
                    flag_wait(&g_cnt[1 * 32], epoch1 * 80);
                    PROF_T(33);
                    const CUtensorMap* mws = kh ? &maps.wsim : &maps.wsre;
                    int s = 0, ph = 1;
                    for (int kb = 0; kb < 44; kb++) {
                        const uint32_t full = sb + B_FULL2 + 8 * s, dst = sb + s * R2_STAGE;
                        if (kb == 32) { PROF_T(34); flag_wait(&g_cnt[(2 + m2 * 2 + kh) * 32], epoch1 * (kh ? 5 : 6)); PROF_T(35); }
                        if (kb == 42 && kh) { PROF_T(36); flag_wait(&g_cnt[(34 + m2) * 32], epoch1); PROF_T(37); }
                        if (kb < R2_N) { if (kb != 3) mbar_wait(sb + B_EMPTY1 + 8 * (kb == 4 ? 3 : kb), 0); }
                        else mbar_wait(sb + B_EMPTY2 + 8 * s, ph);
                        mbar_expect_tx(full, R2_STAGE);
                        if (kb < 32) {
                            tma_2d(dst, mws, kb * 64, m2 * 128, full);
                            tma_2d_mc(dst + 16384 + rank * 10240, &maps.abT_ld, kb * 64, kh * 640 + nb * 160 + rank * 80, full);
                        } else {
                            const int kk = kh * 768 + (kb - 32) * 64;
                            tma_2d(dst, &maps.h, kk, m2 * 128, full);
                            tma_3d_mc(dst + 16384 + rank * 10240, &maps.wdown, 0, kk + rank * 32, nb * 5, full);
                        }
                        if (++s == R2_N) { s = 0; ph ^= 1; }
                    }
                }
            }
        } else if (warp == 9) {
            if (lane == 0) {
                int q = 0;
                for (int r = 0; r < nrounds; r++) {
                    const bool ab = first_ab && r == 0;
                    int m, ct;
                    h_tile(r, m, ct);
                    const int nch = ab ? 4 : 2;
                    for (int c = 0; c < nch; c++, q++) {
                        const int b = q & 1;
                        mbar_wait(sb + B_STGF + 8 * b, (q >> 1) & 1);
                        if (ab) tma_store_2d(&maps.abT_st, sb + STG_OFF + b * STG_SZ, ab_s * 256 + c * 64, ab_e * 128);
                        else tma_store_2d(&maps.h, sb + STG_OFF + b * STG_SZ, ct * 128 + c * 64, m * 128);
                        bulk_commit();
                        bulk_wait_read0();
                        mbar_arrive(sb + B_STGE + 8 * b);
                    }
                    bulk_wait0();
                    unsigned* f = ab ? &g_cnt[1 * 32] : (ct == 11 ? &g_cnt[(34 + m) * 32] : &g_cnt[(2 + m * 2 + (ct >= 6)) * 32]);
                    asm volatile("red.release.gpu.global.add.u32 [%0], 1;" ::"l"(f) : "memory");
                    PROF_T(40 + r);
                }
            }
        } else if (is_main) {
            const int w = warp - 10;
            const uint2* gw2 = reinterpret_cast<const uint2*>(gw);
            uint2 wv[5];
#pragma unroll
            for (int j = 0; j < 5; j++) wv[j] = __ldg(gw2 + j * 32 + lane);
            if (w == 1 && lane == 0) {
                unsigned e = ld_relaxed(&g_cnt[0]) / NCTA + 1;
                asm volatile("st.shared.u32 [%0], %1;" ::"r"(sb + EPOCH_OFF), "r"(e) : "memory");
            }
            const CUtensorMap* mws = kh ? &maps.wsim : &maps.wsre;
#pragma unroll 1
            for (int i = 0; i < 32; i++) {
                const int rl = w * 64 + 2 * i;
                const uint2* xr = reinterpret_cast<const uint2*>(x + (size_t)(m2 * 128 + rl) * D_);
                uint2 a[10];
#pragma unroll
                for (int j = 0; j < 10; j++) a[j] = __ldg(xr + j * 32 + lane);
                if (lane == 0 && i >= 2 && i < 18 && (i & 1) == 0) {
                    if (w == 0) tma_prefetch_2d(mws, (4 * ((i - 2) >> 1) + nb) * 64, m2 * 128);
                    else if (i == 16) bulk_prefetch(wdown + (size_t)blockIdx.x * 7680, 15360);
                }
                float s0 = 0.f, s1 = 0.f;
#pragma unroll
                for (int j = 0; j < 5; j++) {
                    __nv_bfloat162 p;
                    uint32_t u;
                    p = __hmul2(*reinterpret_cast<__nv_bfloat162*>(&a[j].x), *reinterpret_cast<__nv_bfloat162*>(&wv[j].x)); u = *reinterpret_cast<uint32_t*>(&p); s0 += bf_lo(u) + bf_hi(u);
                    p = __hmul2(*reinterpret_cast<__nv_bfloat162*>(&a[j].y), *reinterpret_cast<__nv_bfloat162*>(&wv[j].y)); u = *reinterpret_cast<uint32_t*>(&p); s0 += bf_lo(u) + bf_hi(u);
                    p = __hmul2(*reinterpret_cast<__nv_bfloat162*>(&a[5 + j].x), *reinterpret_cast<__nv_bfloat162*>(&wv[j].x)); u = *reinterpret_cast<uint32_t*>(&p); s1 += bf_lo(u) + bf_hi(u);
                    p = __hmul2(*reinterpret_cast<__nv_bfloat162*>(&a[5 + j].y), *reinterpret_cast<__nv_bfloat162*>(&wv[j].y)); u = *reinterpret_cast<uint32_t*>(&p); s1 += bf_lo(u) + bf_hi(u);
                }
#pragma unroll
                for (int o = 16; o > 0; o >>= 1) { s0 += __shfl_xor_sync(0xffffffffu, s0, o); s1 += __shfl_xor_sync(0xffffffffu, s1, o); }
                if (lane < 2) {
                    float z = __bfloat162float(__float2bfloat16(lane ? s1 : s0));
                    float g = __bfloat162float(__float2bfloat16(__fdividef(1.0f, 1.0f + __expf(-z))));
                    asm volatile("st.shared.f32 [%0], %1;" ::"r"(sb + G_OFF + 4 * (rl + lane)), "f"(g) : "memory");
                }
            }
            __syncwarp();
            if (lane == 0) { mbar_arrive(sb + B_GRDY); PROF_T(44 + w); }
        }
        __syncwarp();
        cluster_arrive_relaxed();
        cluster_wait();
    } else {
        asm volatile("setmaxnreg.inc.sync.aligned.u32 232;");
        const int wg = warp >> 2;
        Ctx c;
        c.sb = sb;
        c.a_off = wg * 8192;
        c.lane = lane;
        {
            const uint32_t row = warp * 16 + (lane & 7) + ((lane >> 3) & 1) * 8;
            c.st_addr = sb + STG_OFF + row * 128;
            c.st_row7 = lane & 7;
            c.st_hi = lane >> 4;
        }
        c.it1 = 0;
        c.q = 0;
        uint32_t pk[64];
        {
            float acc[128];
            if (threadIdx.x == 0) PROF_T(0);
            if (first_ab) tile_plain<0>(acc, c); else tile_plain<1>(acc, c);
            finish_s1(acc, pk, c);
            if (threadIdx.x == 0) PROF_T(1);
            bool prev_ab = first_ab;
#pragma unroll 1
            for (int r = 1; r < nrounds; r++) {
                s1_epi_iter<0>(acc, pk, c, prev_ab); s1_epi_iter<1>(acc, pk, c, prev_ab); s1_epi_iter<2>(acc, pk, c, prev_ab);
                s1_epi_iter<3>(acc, pk, c, prev_ab); s1_epi_iter<4>(acc, pk, c, prev_ab); s1_epi_iter<5>(acc, pk, c, prev_ab);
                s1_epi_iter<6>(acc, pk, c, prev_ab); s1_epi_iter<7>(acc, pk, c, prev_ab); s1_epi_iter<8>(acc, pk, c, prev_ab);
                s1_epi_iter<9>(acc, pk, c, prev_ab);
                finish_s1(acc, pk, c);
                prev_ab = false;
                if (threadIdx.x == 0) PROF_T(1 + r);
            }
        }
        if (!is_main) {
            epi_h<0>(pk, c); epi_h<1>(pk, c); epi_h<2>(pk, c); epi_h<3>(pk, c);
            epi_h<4>(pk, c); epi_h<5>(pk, c); epi_h<6>(pk, c); epi_h<7>(pk, c);
        } else {
            float accY[80], accF[80];
            s2_epi_iter<0>(accY, pk, c); s2_epi_iter<1>(accY, pk, c); s2_epi_iter<2>(accY, pk, c); s2_epi_iter<3>(accY, pk, c);
            s2_epi_iter<4>(accY, pk, c); s2_epi_iter<5>(accY, pk, c); s2_epi_iter<6>(accY, pk, c); s2_epi_iter<7>(accY, pk, c);
            if (threadIdx.x == 0) PROF_T(8);
            int s = 8 % R2_N, ps = 7 % R2_N, ph = (8 / R2_N) & 1;
#pragma unroll 1
            for (int kb = 8; kb < 32; kb++) {
                mbar_wait(sb + B_FULL2 + 8 * s, ph);
                mma_s2<0>(accY, c, s, false);
                wgmma_wait<1>();
                release(sb + B_EMPTY2 + 8 * ps, lane);
                ps = s;
                if (++s == R2_N) { s = 0; ph ^= 1; }
            }
            if (threadIdx.x == 0) PROF_T(9);
            const bool leader = wg == kh;
#pragma unroll 1
            for (int kb = 32; kb < 44; kb++) {
                if (kb == 40 && !leader) bar_sync(1, 256);
                mbar_wait(sb + B_FULL2 + 8 * s, ph);
                mma_s2<1>(accF, c, s, kb == 32);
                if (kb == 43 && leader) bar_arrive(1, 256);
                wgmma_wait<1>();
                if (kb < 40) release(sb + B_EMPTY2 + 8 * ps, lane);
                ps = s;
                if (++s == R2_N) { s = 0; ph ^= 1; }
            }
            mbar_wait(sb + B_GRDY, 0);
            float g0, g1;
            uint32_t tag;
            asm volatile("ld.shared.f32 %0, [%1];" : "=f"(g0) : "r"(sb + G_OFF + 4 * (warp * 16 + (lane >> 2))));
            asm volatile("ld.shared.f32 %0, [%1];" : "=f"(g1) : "r"(sb + G_OFF + 4 * (warp * 16 + (lane >> 2) + 8)));
            asm volatile("ld.shared.u32 %0, [%1];" : "=r"(tag) : "r"(sb + EPOCH_OFF));
            tag &= 3;
            const float f0 = __bfloat162float(__float2bfloat16(1.0f - g0)), f1 = __bfloat162float(__float2bfloat16(1.0f - g1));
            if (kh) { g0 = -g0; g1 = -g1; }
            wgmma_wait<0>();
#pragma unroll
            for (int i = 0; i < 80; i++) asm volatile("" : "+f"(accY[i]), "+f"(accF[i])::"memory");
            if ((threadIdx.x & 127) == 0) PROF_T(10 + (leader ? 0 : 1));
#pragma unroll
            for (int j = 0; j < 20; j++) {
                accY[4 * j + 0] = fmaf(g0, accY[4 * j + 0], f0 * accF[4 * j + 0]);
                accY[4 * j + 1] = fmaf(g0, accY[4 * j + 1], f0 * accF[4 * j + 1]);
                accY[4 * j + 2] = fmaf(g1, accY[4 * j + 2], f1 * accF[4 * j + 2]);
                accY[4 * j + 3] = fmaf(g1, accY[4 * j + 3], f1 * accF[4 * j + 3]);
            }
            const int wl = warp & 3;
            const uint32_t recv = sb + RECV_OFF + wl * 10240;
            if (leader) {
                float4* dst = g_xch + ((size_t)blockIdx.x * 20) * 128 + (threadIdx.x & 127);
#pragma unroll
                for (int j = 0; j < 20; j++) {
                    uint32_t v0 = (__float_as_uint(accY[4 * j + 0]) & ~3u) | tag, v1 = (__float_as_uint(accY[4 * j + 1]) & ~3u) | tag;
                    uint32_t v2 = (__float_as_uint(accY[4 * j + 2]) & ~3u) | tag, v3 = (__float_as_uint(accY[4 * j + 3]) & ~3u) | tag;
                    asm volatile("st.relaxed.gpu.global.v4.b32 [%0], {%1, %2, %3, %4};" ::"l"(dst + j * 128), "r"(v0), "r"(v1), "r"(v2), "r"(v3) : "memory");
                }
                if ((threadIdx.x & 127) == 0) PROF_T(12);
                const float4* src = g_xch + ((size_t)(blockIdx.x ^ 64) * 20) * 128 + (threadIdx.x & 127);
                uint32_t v[80];
                for (int tries = 0;; tries++) {
                    uint32_t bad = 0;
#pragma unroll
                    for (int j = 0; j < 20; j++)
                        asm volatile("ld.relaxed.gpu.global.v4.b32 {%0, %1, %2, %3}, [%4];" : "=r"(v[4 * j]), "=r"(v[4 * j + 1]), "=r"(v[4 * j + 2]), "=r"(v[4 * j + 3]) : "l"(src + j * 128) : "memory");
#pragma unroll
                    for (int i = 0; i < 80; i++) bad |= v[i] ^ tag;
                    if (!__any_sync(0xffffffffu, bad & 3)) break;
                    trap_if(tries > (1 << 20));
                }
#pragma unroll
                for (int j = 0; j < 20; j++)
                    asm volatile("st.shared.v4.b32 [%0], {%1, %2, %3, %4};" ::"r"(recv + j * 512 + lane * 16), "r"(v[4 * j]), "r"(v[4 * j + 1]), "r"(v[4 * j + 2]), "r"(v[4 * j + 3]) : "memory");
                bar_arrive(2 + wl, 64);
                if ((threadIdx.x & 127) == 0) PROF_T(13);
            } else {
                bar_sync(2 + wl, 64);
                if ((threadIdx.x & 127) == 0) PROF_T(14);
                uint32_t o[40];
#pragma unroll
                for (int j = 0; j < 20; j++) {
                    float p0, p1, p2, p3;
                    asm volatile("ld.shared.v4.f32 {%0, %1, %2, %3}, [%4];" : "=f"(p0), "=f"(p1), "=f"(p2), "=f"(p3) : "r"(recv + j * 512 + lane * 16) : "memory");
                    o[2 * j] = pack_bf16(accY[4 * j] + p0, accY[4 * j + 1] + p1);
                    o[2 * j + 1] = pack_bf16(accY[4 * j + 2] + p2, accY[4 * j + 3] + p3);
                }
                __syncwarp();
                const uint32_t row = (lane & 7) + ((lane >> 3) & 1) * 8;
#pragma unroll
                for (int p = 0; p < 10; p++) {
                    const uint32_t cg = (p & 1) * 2 + (lane >> 4);
                    stmatrix_x4(recv + (p >> 1) * 1024 + row * 64 + ((cg ^ ((row >> 1) & 3)) << 4), o[4 * p], o[4 * p + 1], o[4 * p + 2], o[4 * p + 3]);
                }
                fence_async_smem();
                __syncwarp();
                if (lane == 0) {
                    tma_store_3d(&maps.out, recv, 0, m2 * 128 + warp * 16, nb * 5);
                    bulk_commit();
                    bulk_wait_read0();
                }
                if ((threadIdx.x & 127) == 0) PROF_T(15);
            }
        }
        __syncwarp();
        cluster_arrive_relaxed();
        cluster_wait();
        if (threadIdx.x == 0) {
            atomicAdd(&g_cnt[0], 1u);
            PROF_T(16);
        }
    }
}

typedef CUresult (*EncodeFn)(CUtensorMap*, CUtensorMapDataType, cuuint32_t, void*, const cuuint64_t*, const cuuint64_t*, const cuuint32_t*,
                             const cuuint32_t*, CUtensorMapInterleave, CUtensorMapSwizzle, CUtensorMapL2promotion, CUtensorMapFloatOOBfill);

static void enc(EncodeFn fn, CUtensorMap* m, const void* ptr, int rank, cuuint64_t d0, cuuint64_t d1, cuuint64_t d2, cuuint64_t s1, cuuint64_t s2,
                cuuint32_t b0, cuuint32_t b1, cuuint32_t b2, CUtensorMapSwizzle swz) {
    cuuint64_t dims[3] = {d0, d1, d2}, strides[2] = {s1, s2};
    cuuint32_t box[3] = {b0, b1, b2}, es[3] = {1, 1, 1};
    fn(m, CU_TENSOR_MAP_DATA_TYPE_BFLOAT16, rank, const_cast<void*>(ptr), dims, strides, box, es, CU_TENSOR_MAP_INTERLEAVE_NONE, swz,
       CU_TENSOR_MAP_L2_PROMOTION_L2_256B, CU_TENSOR_MAP_FLOAT_OOB_FILL_NONE);
}

extern "C" void kernel_launch(void* const* d_in, const int* in_sizes, int n_in, void* d_out, int out_size) {
    (void)in_sizes; (void)n_in; (void)out_size;
    const bf16* x = (const bf16*)d_in[0];
    const bf16* wsre = (const bf16*)d_in[1];
    const bf16* wsim = (const bf16*)d_in[2];
    const bf16* wdre = (const bf16*)d_in[3];
    const bf16* wdim = (const bf16*)d_in[4];
    const bf16* wg = (const bf16*)d_in[6];
    const bf16* wu = (const bf16*)d_in[7];
    const bf16* wdown = (const bf16*)d_in[8];
    const bf16* gw = (const bf16*)d_in[9];

    void* fnp = nullptr;
    cudaDriverEntryPointQueryResult qr;
    cudaGetDriverEntryPoint("cuTensorMapEncodeTiled", &fnp, cudaEnableDefault, &qr);
    EncodeFn fn = (EncodeFn)fnp;
    void *abT, *H;
    cudaGetSymbolAddress(&abT, g_abT);
    cudaGetSymbolAddress(&H, g_H);

    Maps mp;
    const CUtensorMapSwizzle S128 = CU_TENSOR_MAP_SWIZZLE_128B, S64 = CU_TENSOR_MAP_SWIZZLE_64B;
    enc(fn, &mp.x, x, 2, D_, S_, 1, D_ * 2, 0, 64, 128, 1, S128);
    enc(fn, &mp.wdre, wdre, 2, D_, D_, 1, D_ * 2, 0, 64, 128, 1, S128);
    enc(fn, &mp.wdim, wdim, 2, D_, D_, 1, D_ * 2, 0, 64, 128, 1, S128);
    enc(fn, &mp.wg, wg, 3, 64, D_, F_ / 64, F_ * 2, 128, 64, 64, 2, S128);
    enc(fn, &mp.wu, wu, 3, 64, D_, F_ / 64, F_ * 2, 128, 64, 64, 2, S128);
    enc(fn, &mp.wsre, wsre, 2, S_, S_, 1, S_ * 2, 0, 64, 128, 1, S128);
    enc(fn, &mp.wsim, wsim, 2, S_, S_, 1, S_ * 2, 0, 64, 128, 1, S128);
    enc(fn, &mp.abT_ld, abT, 2, S_, 2 * D_, 1, S_ * 2, 0, 64, 80, 1, S128);
    enc(fn, &mp.abT_st, abT, 2, S_, 2 * D_, 1, S_ * 2, 0, 64, 128, 1, S128);
    enc(fn, &mp.h, H, 2, F_, S_, 1, F_ * 2, 0, 64, 128, 1, S128);
    enc(fn, &mp.wdown, wdown, 3, 32, F_, D_ / 32, D_ * 2, 64, 32, 32, 5, S64);
    enc(fn, &mp.out, d_out, 3, 32, S_, D_ / 32, D_ * 2, 64, 32, 16, 5, S64);

    cudaFuncSetAttribute(fused_kernel, cudaFuncAttributeMaxDynamicSharedMemorySize, SMEM_BYTES);
    fused_kernel<<<NCTA, 384, SMEM_BYTES>>>(mp, x, gw, wdown);
}
```

```cpp
#include <cuda_runtime.h>
#include <cuda_bf16.h>
#include <cuda.h>
#include <stdint.h>

typedef __nv_bfloat16 bf16;

constexpr int S_ = 2048, D_ = 640, F_ = 1536;
constexpr int NCTA = 132;
#define LAG 4
#define PROMO CU_TENSOR_MAP_L2_PROMOTION_L2_128B
#define NPRE 1
#define AB2_ITER 4

__device__ bf16 g_abT[2 * D_ * S_];
__device__ bf16 g_H[S_ * F_];
__device__ float g_gate[S_];
__device__ unsigned g_cnt[80 * 32];
#define PROF_T(idx) do { } while (0)
#define PROF_C(idx) do { } while (0)

struct Maps {
    CUtensorMap x, wdre, wdim, wg, wu, wsre, wsim, abT, abT_st, h, h_st, wdown, out;
    uint32_t tab[NCTA];
};

constexpr int R1_STAGE = 49152, R1_N = 4;
constexpr int R2_STAGE = 36864, R2_N = 5;
constexpr int STG_OFF = 196608, STG_SZ = 16384;
constexpr int OUT_OFF = 184320;
constexpr int BAR_OFF = 229376;
constexpr int B_FULL1 = BAR_OFF, B_EMPTY1 = BAR_OFF + 32, B_FULL2 = BAR_OFF + 64, B_EMPTY2 = BAR_OFF + 104;
constexpr int B_STGF = BAR_OFF + 208  , B_STGE = BAR_OFF + 160, B_DEP_AB = BAR_OFF + 168, B_DEP_H = BAR_OFF + 176, B_DEP_LATE = BAR_OFF + 184, B_GRDY = BAR_OFF + 192, B_DEP_AB2 = BAR_OFF + 200;
constexpr int G_OFF = BAR_OFF + 256;
constexpr int SMEM_BYTES = BAR_OFF + 1024;

__device__ __forceinline__ void trap_if(uint32_t cond) { asm volatile("{\n.reg .pred p;\nsetp.ne.u32 p, %0, 0;\n@p trap;\n}" ::"r"(cond)); }
__device__ __forceinline__ uint32_t smem_u32(const void* p) { return (uint32_t)__cvta_generic_to_shared(p); }
__device__ __forceinline__ void mbar_init(uint32_t bar, int count) { asm volatile("mbarrier.init.shared::cta.b64 [%0], %1;" ::"r"(bar), "r"(count)); }
__device__ __forceinline__ void mbar_expect_tx(uint32_t bar, uint32_t bytes) {
    asm volatile("mbarrier.arrive.expect_tx.shared::cta.b64 _, [%0], %1;" ::"r"(bar), "r"(bytes) : "memory");
}
__device__ __forceinline__ void mbar_arrive(uint32_t bar) { asm volatile("mbarrier.arrive.shared::cta.b64 _, [%0];" ::"r"(bar) : "memory"); }
__device__ __forceinline__ void mbar_arrive_cluster(uint32_t bar, uint32_t cta) {
    asm volatile("{\n.reg .b32 ra;\nmapa.shared::cluster.u32 ra, %0, %1;\nmbarrier.arrive.shared::cluster.b64 _, [ra];\n}" ::"r"(bar), "r"(cta) : "memory");
}
__device__ __forceinline__ void mbar_wait(uint32_t bar, uint32_t parity) {
    asm volatile(
        "{\n.reg .pred p;\n.reg .u32 n;\nmov.u32 n, 0;\nLAB_WAIT:\n"
        "mbarrier.try_wait.parity.shared::cta.b64 p, [%0], %1;\n@p bra DONE;\n"
        "add.u32 n, n, 1;\nsetp.lt.u32 p, n, 1048576;\n@p bra LAB_WAIT;\ntrap;\nDONE:\n}" ::"r"(bar), "r"(parity) : "memory");
}
__device__ __forceinline__ void flag_wait(const unsigned* p, unsigned target) {
    asm volatile(
        "{\n.reg .pred p;\n.reg .u32 n, v;\n.reg .s32 d;\nmov.u32 n, 0;\nLAB_WAIT:\n"
        "ld.acquire.gpu.global.u32 v, [%0];\nsub.s32 d, v, %1;\nsetp.ge.s32 p, d, 0;\n@p bra DONE;\n"
        "add.u32 n, n, 1;\nsetp.lt.u32 p, n, 4194304;\n@p bra LAB_WAIT;\ntrap;\nDONE:\n}" ::"l"(p), "r"(target) : "memory");
}
#define RFENCE "fence.proxy.async.global;"
__device__ __forceinline__ void fence_async_global() { asm volatile(RFENCE ::: "memory"); }
__device__ __forceinline__ unsigned ld_relaxed(const unsigned* p) {
    unsigned v;
    asm volatile("ld.relaxed.gpu.global.u32 %0, [%1];" : "=r"(v) : "l"(p) : "memory");
    return v;
}
__device__ __forceinline__ void tma_2d(uint32_t dst, const CUtensorMap* tm, int c0, int c1, uint32_t bar) {
    asm volatile("cp.async.bulk.tensor.2d.shared::cluster.global.mbarrier::complete_tx::bytes [%0], [%1, {%3, %4}], [%2];" ::"r"(dst), "l"(tm), "r"(bar), "r"(c0), "r"(c1) : "memory");
}
__device__ __forceinline__ void tma_2d_mc(uint32_t dst, const CUtensorMap* tm, int c0, int c1, uint32_t bar) {
    asm volatile("cp.async.bulk.tensor.2d.shared::cluster.global.mbarrier::complete_tx::bytes.multicast::cluster [%0], [%1, {%3, %4}], [%2], %5;" ::"r"(dst), "l"(tm), "r"(bar), "r"(c0), "r"(c1), "h"((uint16_t)3) : "memory");
}
__device__ __forceinline__ void tma_3d_mc(uint32_t dst, const CUtensorMap* tm, int c0, int c1, int c2, uint32_t bar) {
    asm volatile("cp.async.bulk.tensor.3d.shared::cluster.global.mbarrier::complete_tx::bytes.multicast::cluster [%0], [%1, {%3, %4, %5}], [%2], %6;" ::"r"(dst), "l"(tm), "r"(bar), "r"(c0), "r"(c1), "r"(c2), "h"((uint16_t)3) : "memory");
}
__device__ __forceinline__ void tma_3d(uint32_t dst, const CUtensorMap* tm, int c0, int c1, int c2, uint32_t bar) {
    asm volatile("cp.async.bulk.tensor.3d.shared::cluster.global.mbarrier::complete_tx::bytes [%0], [%1, {%3, %4, %5}], [%2];" ::"r"(dst), "l"(tm), "r"(bar), "r"(c0), "r"(c1), "r"(c2) : "memory");
}
__device__ __forceinline__ void e_expect_tma_2d(uint32_t bar, uint32_t bytes, uint32_t dst, const CUtensorMap* tm, int c0, int c1) {
    asm volatile("{\n.reg .pred p;\nelect.sync _|p, 0xffffffff;\n"
        "@p mbarrier.arrive.expect_tx.shared::cta.b64 _, [%2], %5;\n"
        "@p cp.async.bulk.tensor.2d.shared::cluster.global.mbarrier::complete_tx::bytes [%0], [%1, {%3, %4}], [%2];\n}"
        ::"r"(dst), "l"(tm), "r"(bar), "r"(c0), "r"(c1), "r"(bytes) : "memory");
}
__device__ __forceinline__ void e_tma_2d(uint32_t dst, const CUtensorMap* tm, int c0, int c1, uint32_t bar) {
    asm volatile("{\n.reg .pred p;\nelect.sync _|p, 0xffffffff;\n"
        "@p cp.async.bulk.tensor.2d.shared::cluster.global.mbarrier::complete_tx::bytes [%0], [%1, {%3, %4}], [%2];\n}"
        ::"r"(dst), "l"(tm), "r"(bar), "r"(c0), "r"(c1) : "memory");
}
__device__ __forceinline__ void e_tma_3d(uint32_t dst, const CUtensorMap* tm, int c0, int c1, int c2, uint32_t bar) {
    asm volatile("{\n.reg .pred p;\nelect.sync _|p, 0xffffffff;\n"
        "@p cp.async.bulk.tensor.3d.shared::cluster.global.mbarrier::complete_tx::bytes [%0], [%1, {%3, %4, %5}], [%2];\n}"
        ::"r"(dst), "l"(tm), "r"(bar), "r"(c0), "r"(c1), "r"(c2) : "memory");
}
__device__ __forceinline__ void e_tma_2d_mc(uint32_t dst, const CUtensorMap* tm, int c0, int c1, uint32_t bar) {
    asm volatile("{\n.reg .pred p;\nelect.sync _|p, 0xffffffff;\n"
        "@p cp.async.bulk.tensor.2d.shared::cluster.global.mbarrier::complete_tx::bytes.multicast::cluster [%0], [%1, {%3, %4}], [%2], %5;\n}"
        ::"r"(dst), "l"(tm), "r"(bar), "r"(c0), "r"(c1), "h"((uint16_t)3) : "memory");
}
__device__ __forceinline__ void e_tma_3d_mc(uint32_t dst, const CUtensorMap* tm, int c0, int c1, int c2, uint32_t bar) {
    asm volatile("{\n.reg .pred p;\nelect.sync _|p, 0xffffffff;\n"
        "@p cp.async.bulk.tensor.3d.shared::cluster.global.mbarrier::complete_tx::bytes.multicast::cluster [%0], [%1, {%3, %4, %5}], [%2], %6;\n}"
        ::"r"(dst), "l"(tm), "r"(bar), "r"(c0), "r"(c1), "r"(c2), "h"((uint16_t)3) : "memory");
}
__device__ __forceinline__ void tma_store_2d(const CUtensorMap* tm, uint32_t src, int c0, int c1) {
    asm volatile("cp.async.bulk.tensor.2d.global.shared::cta.bulk_group [%0, {%2, %3}], [%1];" ::"l"(tm), "r"(src), "r"(c0), "r"(c1) : "memory");
}
__device__ __forceinline__ void tma_reduce_add_3d(const CUtensorMap* tm, uint32_t src, int c0, int c1, int c2) {
    asm volatile("cp.reduce.async.bulk.tensor.3d.global.shared::cta.add.tile.bulk_group [%0, {%2, %3, %4}], [%1];" ::"l"(tm), "r"(src), "r"(c0), "r"(c1), "r"(c2) : "memory");
}
__device__ __forceinline__ void flag_publish(unsigned* f) {
    asm volatile("fence.acq_rel.gpu;\nred.relaxed.gpu.global.add.u32 [%0], 1;" ::"l"(f) : "memory");
}
__device__ __forceinline__ void tma_prefetch_2d(const CUtensorMap* tm, int c0, int c1) {
    asm volatile("cp.async.bulk.prefetch.tensor.2d.L2.global [%0, {%1, %2}];" ::"l"(tm), "r"(c0), "r"(c1) : "memory");
}
__device__ __forceinline__ void bulk_prefetch(const void* p, uint32_t bytes) {
    asm volatile("cp.async.bulk.prefetch.L2.global [%0], %1;" ::"l"(p), "r"(bytes) : "memory");
}
__device__ __forceinline__ void prefetch_map(const CUtensorMap* tm) { asm volatile("prefetch.tensormap [%0];" ::"l"(tm) : "memory"); }
__device__ __forceinline__ void bulk_commit() { asm volatile("cp.async.bulk.commit_group;" ::: "memory"); }
__device__ __forceinline__ void bulk_wait_read0() { asm volatile("cp.async.bulk.wait_group.read 0;" ::: "memory"); }
__device__ __forceinline__ void bulk_wait0() { asm volatile("cp.async.bulk.wait_group 0;" ::: "memory"); }
__device__ __forceinline__ void fence_async_smem() { asm volatile("fence.proxy.async.shared::cta;" ::: "memory"); }
__device__ __forceinline__ void wgmma_fence() { asm volatile("wgmma.fence.sync.aligned;" ::: "memory"); }
__device__ __forceinline__ void wgmma_commit() { asm volatile("wgmma.commit_group.sync.aligned;" ::: "memory"); }
template <int N> __device__ __forceinline__ void wgmma_wait() { asm volatile("wgmma.wait_group.sync.aligned %0;" ::"n"(N) : "memory"); }
__device__ __forceinline__ void cluster_arrive_relaxed() { asm volatile("barrier.cluster.arrive.relaxed.aligned;" ::: "memory"); }
__device__ __forceinline__ void cluster_wait() { asm volatile("barrier.cluster.wait.acquire.aligned;" ::: "memory"); }
__device__ __forceinline__ void bar_sync(int id, int n) { asm volatile("bar.sync %0, %1;" ::"r"(id), "r"(n) : "memory"); }
__device__ __forceinline__ void bar_arrive(int id, int n) { asm volatile("bar.arrive %0, %1;" ::"r"(id), "r"(n) : "memory"); }
__device__ __forceinline__ uint64_t mk_desc(uint32_t lo, uint32_t hi) {
    uint64_t d;
    asm("mov.b64 %0, {%1, %2};" : "=l"(d) : "r"(lo), "r"(hi));
    return d;
}
__device__ __forceinline__ void stmatrix_x4(uint32_t addr, uint32_t r0, uint32_t r1, uint32_t r2, uint32_t r3) {
    asm volatile("stmatrix.sync.aligned.m8n8.x4.shared.b16 [%0], {%1, %2, %3, %4};" ::"r"(addr), "r"(r0), "r"(r1), "r"(r2), "r"(r3) : "memory");
}
__device__ __forceinline__ uint32_t pack_bf16(float lo, float hi) {
    uint32_t r;
    asm("cvt.rn.bf16x2.f32 %0, %1, %2;" : "=r"(r) : "f"(hi), "f"(lo));
    return r;
}
__device__ __forceinline__ float bf_lo(uint32_t v) { return __uint_as_float(v << 16); }
__device__ __forceinline__ float bf_hi(uint32_t v) { return __uint_as_float(v & 0xffff0000u); }
__device__ __forceinline__ float geglu(float x, float u) {
    float z = fmaf(x * x, 0.7978845608028654f * 0.044715f, 0.7978845608028654f) * x, th;
    asm("tanh.approx.f32 %0, %1;" : "=f"(th) : "f"(z));
    const float hp = (0.5f * x) * u;
    return fmaf(hp, th, hp);
    const float c0 = -2.0f * 0.7978845608028654f * 1.4426950408889634f;
    const float c1 = c0 * 0.044715f;
    float t = fmaf(x * x, c1, c0) * x, e, r;
    asm("ex2.approx.ftz.f32 %0, %1;" : "=f"(e) : "f"(t));
    asm("rcp.approx.ftz.f32 %0, %1;" : "=f"(r) : "f"(1.0f + e));
    return (x * u) * r;
}
__device__ __forceinline__ uint32_t geglu2(uint32_t g, uint32_t u) { return pack_bf16(geglu(bf_lo(g), bf_lo(u)), geglu(bf_hi(g), bf_hi(u))); }

template <int TB>
__device__ __forceinline__ void wgmma_n256(float (&d)[128], uint64_t da, uint64_t db, int scale_d) {
    asm volatile(
        "{\n.reg .pred p;\nsetp.ne.b32 p, %130, 0;\n"
        "wgmma.mma_async.sync.aligned.m64n256k16.f32.bf16.bf16 {"
        "%0, %1, %2, %3, %4, %5, %6, %7, %8, %9, %10, %11, %12, %13, %14, %15, %16, %17, %18, %19, %20, %21, %22, %23, %24, %25, %26, %27, %28, %29, %30, %31, "
        "%32, %33, %34, %35, %36, %37, %38, %39, %40, %41, %42, %43, %44, %45, %46, %47, %48, %49, %50, %51, %52, %53, %54, %55, %56, %57, %58, %59, %60, %61, "
        "%62, %63, %64, %65, %66, %67, %68, %69, %70, %71, %72, %73, %74, %75, %76, %77, %78, %79, %80, %81, %82, %83, %84, %85, %86, %87, %88, %89, %90, %91, "
        "%92, %93, %94, %95, %96, %97, %98, %99, %100, %101, %102, %103, %104, %105, %106, %107, %108, %109, %110, %111, %112, %113, %114, %115, %116, %117, "
        "%118, %119, %120, %121, %122, %123, %124, %125, %126, %127"
        "}, %128, %129, p, 1, 1, 0, %131;\n}\n"
        : "+f"(d[0]), "+f"(d[1]), "+f"(d[2]), "+f"(d[3]), "+f"(d[4]), "+f"(d[5]), "+f"(d[6]), "+f"(d[7]), "+f"(d[8]), "+f"(d[9]), "+f"(d[10]), "+f"(d[11]),
          "+f"(d[12]), "+f"(d[13]), "+f"(d[14]), "+f"(d[15]), "+f"(d[16]), "+f"(d[17]), "+f"(d[18]), "+f"(d[19]), "+f"(d[20]), "+f"(d[21]), "+f"(d[22]),
          "+f"(d[23]), "+f"(d[24]), "+f"(d[25]), "+f"(d[26]), "+f"(d[27]), "+f"(d[28]), "+f"(d[29]), "+f"(d[30]), "+f"(d[31]), "+f"(d[32]), "+f"(d[33]),
          "+f"(d[34]), "+f"(d[35]), "+f"(d[36]), "+f"(d[37]), "+f"(d[38]), "+f"(d[39]), "+f"(d[40]), "+f"(d[41]), "+f"(d[42]), "+f"(d[43]), "+f"(d[44]),
          "+f"(d[45]), "+f"(d[46]), "+f"(d[47]), "+f"(d[48]), "+f"(d[49]), "+f"(d[50]), "+f"(d[51]), "+f"(d[52]), "+f"(d[53]), "+f"(d[54]), "+f"(d[55]),
          "+f"(d[56]), "+f"(d[57]), "+f"(d[58]), "+f"(d[59]), "+f"(d[60]), "+f"(d[61]), "+f"(d[62]), "+f"(d[63]), "+f"(d[64]), "+f"(d[65]), "+f"(d[66]),
          "+f"(d[67]), "+f"(d[68]), "+f"(d[69]), "+f"(d[70]), "+f"(d[71]), "+f"(d[72]), "+f"(d[73]), "+f"(d[74]), "+f"(d[75]), "+f"(d[76]), "+f"(d[77]),
          "+f"(d[78]), "+f"(d[79]), "+f"(d[80]), "+f"(d[81]), "+f"(d[82]), "+f"(d[83]), "+f"(d[84]), "+f"(d[85]), "+f"(d[86]), "+f"(d[87]), "+f"(d[88]),
          "+f"(d[89]), "+f"(d[90]), "+f"(d[91]), "+f"(d[92]), "+f"(d[93]), "+f"(d[94]), "+f"(d[95]), "+f"(d[96]), "+f"(d[97]), "+f"(d[98]), "+f"(d[99]),
          "+f"(d[100]), "+f"(d[101]), "+f"(d[102]), "+f"(d[103]), "+f"(d[104]), "+f"(d[105]), "+f"(d[106]), "+f"(d[107]), "+f"(d[108]), "+f"(d[109]),
          "+f"(d[110]), "+f"(d[111]), "+f"(d[112]), "+f"(d[113]), "+f"(d[114]), "+f"(d[115]), "+f"(d[116]), "+f"(d[117]), "+f"(d[118]), "+f"(d[119]),
          "+f"(d[120]), "+f"(d[121]), "+f"(d[122]), "+f"(d[123]), "+f"(d[124]), "+f"(d[125]), "+f"(d[126]), "+f"(d[127])
        : "l"(da), "l"(db), "r"(scale_d), "n"(TB));
}
template <int TB>
__device__ __forceinline__ void wgmma_n160(float (&d)[80], uint64_t da, uint64_t db, int scale_d) {
    asm volatile(
        "{\n.reg .pred p;\nsetp.ne.b32 p, %82, 0;\n"
        "wgmma.mma_async.sync.aligned.m64n160k16.f32.bf16.bf16 {"
        "%0, %1, %2, %3, %4, %5, %6, %7, %8, %9, %10, %11, %12, %13, %14, %15, %16, %17, %18, %19, %20, %21, %22, %23, %24, %25, %26, %27, %28, %29, %30, %31, "
        "%32, %33, %34, %35, %36, %37, %38, %39, %40, %41, %42, %43, %44, %45, %46, %47, %48, %49, %50, %51, %52, %53, %54, %55, %56, %57, %58, %59, %60, %61, "
        "%62, %63, %64, %65, %66, %67, %68, %69, %70, %71, %72, %73, %74, %75, %76, %77, %78, %79"
        "}, %80, %81, p, 1, 1, 0, %83;\n}\n"
        : "+f"(d[0]), "+f"(d[1]), "+f"(d[2]), "+f"(d[3]), "+f"(d[4]), "+f"(d[5]), "+f"(d[6]), "+f"(d[7]), "+f"(d[8]), "+f"(d[9]), "+f"(d[10]), "+f"(d[11]),
          "+f"(d[12]), "+f"(d[13]), "+f"(d[14]), "+f"(d[15]), "+f"(d[16]), "+f"(d[17]), "+f"(d[18]), "+f"(d[19]), "+f"(d[20]), "+f"(d[21]), "+f"(d[22]),
          "+f"(d[23]), "+f"(d[24]), "+f"(d[25]), "+f"(d[26]), "+f"(d[27]), "+f"(d[28]), "+f"(d[29]), "+f"(d[30]), "+f"(d[31]), "+f"(d[32]), "+f"(d[33]),
          "+f"(d[34]), "+f"(d[35]), "+f"(d[36]), "+f"(d[37]), "+f"(d[38]), "+f"(d[39]), "+f"(d[40]), "+f"(d[41]), "+f"(d[42]), "+f"(d[43]), "+f"(d[44]),
          "+f"(d[45]), "+f"(d[46]), "+f"(d[47]), "+f"(d[48]), "+f"(d[49]), "+f"(d[50]), "+f"(d[51]), "+f"(d[52]), "+f"(d[53]), "+f"(d[54]), "+f"(d[55]),
          "+f"(d[56]), "+f"(d[57]), "+f"(d[58]), "+f"(d[59]), "+f"(d[60]), "+f"(d[61]), "+f"(d[62]), "+f"(d[63]), "+f"(d[64]), "+f"(d[65]), "+f"(d[66]),
          "+f"(d[67]), "+f"(d[68]), "+f"(d[69]), "+f"(d[70]), "+f"(d[71]), "+f"(d[72]), "+f"(d[73]), "+f"(d[74]), "+f"(d[75]), "+f"(d[76]), "+f"(d[77]),
          "+f"(d[78]), "+f"(d[79])
        : "l"(da), "l"(db), "r"(scale_d), "n"(TB));
}

constexpr uint32_t DH_128 = (1024 >> 4) | (1u << 30);
constexpr uint32_t DH_64 = (512 >> 4) | (2u << 30);
constexpr uint32_t DL_K = 1u << 16;
constexpr uint32_t DL_N128 = (8192u >> 4) << 16;
constexpr uint32_t DL_N64 = (2048u >> 4) << 16;

struct Ctx {
    uint32_t sb;
    uint32_t a_off;
    uint32_t d16;
    uint32_t on;
    uint32_t st_addr;
    uint32_t lane;
    uint32_t rel;
    int it1;
    int q;
};

__device__ __forceinline__ void release(const Ctx& c, uint32_t off) {
    if (c.lane < 2) asm volatile("mbarrier.arrive.shared::cluster.b64 _, [%0];" ::"r"(c.rel + off) : "memory");
}

template <int TB>
__device__ __forceinline__ void mma_s1(float (&acc)[128], const Ctx& c, int s, bool first) {
    const uint32_t lb = c.d16 + s * (R1_STAGE >> 4) + (16384 >> 4) + (TB ? DL_N128 : DL_K);
    const uint32_t la = c.d16 + s * (R1_STAGE >> 4) + (c.a_off >> 4) + DL_K;
    wgmma_fence();
#pragma unroll
    for (int k = 0; k < 4; k++)
        wgmma_n256<TB>(acc, mk_desc(la + k * 2, DH_128), mk_desc(lb + k * (TB ? 128 : 2), DH_128), (k == 0 && first) ? 0 : 1);
    wgmma_commit();
}
template <int TB>
__device__ __forceinline__ void mma_s2(float (&acc)[80], const Ctx& c, int s, bool first) {
    const uint32_t lb = c.d16 + s * (R2_STAGE >> 4) + (16384 >> 4) + (TB ? DL_N64 : DL_K);
    const uint32_t la = c.d16 + s * (R2_STAGE >> 4) + (c.a_off >> 4) + DL_K;
    wgmma_fence();
#pragma unroll
    for (int k = 0; k < 4; k++)
        wgmma_n160<TB>(acc, mk_desc(la + k * 2, DH_128), TB ? mk_desc(lb + (k >> 1) * 640 + (k & 1) * 64, DH_64) : mk_desc(lb + k * 2, DH_128),
                       (k == 0 && first) ? 0 : 1);
    wgmma_commit();
}

__device__ __forceinline__ void stg_acquire(const Ctx& c) { mbar_wait(c.sb + B_STGE, (c.q & 1) ^ 1); }
__device__ __forceinline__ void stg_publish(const Ctx& c, int b) {
    fence_async_smem();
    __syncwarp();
    if (c.lane == 0) mbar_arrive(c.sb + B_STGF + (c.a_off >> 9) + 8 * b);
}
__device__ __forceinline__ void stg_store(const Ctx& c, int b, int p, uint32_t r0, uint32_t r1, uint32_t r2, uint32_t r3) {
    stmatrix_x4((c.st_addr ^ (p << 5)) + b * STG_SZ, r0, r1, r2, r3);
}
template <int I>
__device__ __forceinline__ void epi_h(uint32_t (&pk)[64], Ctx& c) {
    if (I == 0) stg_acquire(c);
#pragma unroll
    for (int j = 0; j < 4; j++) asm volatile("" : "+r"(pk[4 * I + j]), "+r"(pk[32 + 4 * I + j]));
    uint32_t r0 = geglu2(pk[4 * I + 0], pk[32 + 4 * I + 0]);
    uint32_t r1 = geglu2(pk[4 * I + 1], pk[32 + 4 * I + 1]);
    uint32_t r2 = geglu2(pk[4 * I + 2], pk[32 + 4 * I + 2]);
    uint32_t r3 = geglu2(pk[4 * I + 3], pk[32 + 4 * I + 3]);
    stg_store(c, I >> 2, I & 3, r0, r1, r2, r3);
    if (I == 3 || I == 7) stg_publish(c, I >> 2);
    if (I == 7) c.q++;
}
template <int J>
__device__ __forceinline__ void epi_h_half(uint32_t (&pk)[64], Ctx& c) {
    if (J == 0) stg_acquire(c);
    pk[2 * J] = geglu2(pk[2 * J], pk[32 + 2 * J]);
    pk[2 * J + 1] = geglu2(pk[2 * J + 1], pk[32 + 2 * J + 1]);
    if (J & 1) {
        constexpr int I = J >> 1;
        stg_store(c, I >> 2, I & 3, pk[4 * I], pk[4 * I + 1], pk[4 * I + 2], pk[4 * I + 3]);
        if (I == 3 || I == 7) stg_publish(c, I >> 2);
    } else {
        asm volatile("" : "+r"(pk[2 * J]), "+r"(pk[2 * J + 1]));
    }
}
template <int H>
__device__ __forceinline__ void epi_ab(uint32_t (&pk)[64], Ctx& c) {
    stg_acquire(c);
#pragma unroll
    for (int b = 0; b < 2; b++) {
#pragma unroll
        for (int p = 0; p < 4; p++) {
            const int i = 32 * H + 16 * b + 4 * p;
            stg_store(c, b, p, pk[i], pk[i + 1], pk[i + 2], pk[i + 3]);
        }
    }
    fence_async_smem();
    __syncwarp();
    if (c.lane < 2) mbar_arrive(c.sb + B_STGF + (c.a_off >> 9) + 8 * c.lane);
    c.q++;
}
template <int I>
__device__ __forceinline__ void epi_step(uint32_t (&pk)[64], Ctx& c, bool prev_ab) {
    if (prev_ab) {
        if (I == 0) epi_ab<0>(pk, c);
        if (I == AB2_ITER) epi_ab<1>(pk, c);
    } else {
        if (I < 8) epi_h<(I < 8 ? I : 0)>(pk, c);
    }
}
__device__ __forceinline__ void finish_s1(float (&acc)[128], uint32_t (&pk)[64], Ctx& c) {
    wgmma_wait<0>();
    release(c, B_EMPTY1 + 8 * ((c.it1 - 1) & 3));
#pragma unroll
    for (int i = 0; i < 128; i++) asm volatile("" : "+f"(acc[i])::"memory");
#pragma unroll
    for (int i = 0; i < 64; i++) pk[i] = pack_bf16(acc[2 * i], acc[2 * i + 1]);
}
__device__ __forceinline__ void order_wait(const Ctx& c) {
    if (c.a_off) asm volatile("bar.sync 1, 256;" ::: "memory");
}
__device__ __forceinline__ void order_arrive(const Ctx& c) {
    if (!c.a_off) asm volatile("bar.arrive 1, 256;" ::: "memory");
}
template <int TB>
__device__ __forceinline__ void tile_plain(float (&acc)[128], Ctx& c) {
#pragma unroll 1
    for (int kb = 0; kb < 10; kb++) {
        const int s = c.it1 & 3;
        mbar_wait(c.sb + B_FULL1 + 8 * s, (c.it1 >> 2) & 1);
        if (kb == 9) order_wait(c);
        mma_s1<TB>(acc, c, s, kb == 0);
        if (kb == 9) order_arrive(c);
        wgmma_wait<1>();
        if (kb > 0) release(c, B_EMPTY1 + 8 * ((s - 1) & 3));
        c.it1++;
    }
}
template <int I>
__device__ __forceinline__ void s1_epi_iter(float (&acc)[128], uint32_t (&pk)[64], Ctx& c, bool prev_ab) {
    const int s = c.it1 & 3;
    mbar_wait(c.sb + B_FULL1 + 8 * s, (c.it1 >> 2) & 1);
    if (I == 9) order_wait(c);
    mma_s1<1>(acc, c, s, I == 0);
    if (I == 9) order_arrive(c);
    wgmma_wait<1>();
    if (I > 0) release(c, B_EMPTY1 + 8 * ((s - 1) & 3));
    c.it1++;
    epi_step<I>(pk, c, prev_ab);
}
template <int I>
__device__ __forceinline__ void s2_epi_iter(float (&acc)[80], uint32_t (&pk)[64], Ctx& c) {
    constexpr int s = I % R2_N;
    mbar_wait(c.sb + B_FULL2 + 8 * s, (I / R2_N) & 1);
    mma_s2<0>(acc, c, s, I == 0);
    wgmma_wait<1>();
    if (I > 0) release(c, B_EMPTY2 + 8 * ((I + R2_N - 1) % R2_N));
    if (I > 0 && c.on) epi_h_half<(I > 0 ? I - 1 : 0)>(pk, c);
}

__global__ void __cluster_dims__(2, 1, 1) __launch_bounds__(384, 1)
fused_kernel(const __grid_constant__ Maps maps, const bf16* __restrict__ x, const bf16* __restrict__ gw, const bf16* __restrict__ wdown,
             bf16* __restrict__ out) {
    extern __shared__ __align__(1024) uint8_t smem_raw[];
    const uint32_t sb = smem_u32(smem_raw);
    const int warp = __shfl_sync(0xffffffffu, threadIdx.x >> 5, 0);
    const uint32_t lane = threadIdx.x & 31;
    const uint32_t tw = maps.tab[blockIdx.x];
    const bool first_ab = tw & 1;
    const int a0 = (tw >> 4) & 15, b0 = (tw >> 8) & 15;
    if (warp == 0) {
        if (lane == 0) {
#pragma unroll
            for (int s = 0; s < NPRE; s++) mbar_init(sb + B_FULL1 + 8 * s, 1);
            asm volatile("fence.mbarrier_init.release.cluster;" ::: "memory");
        }
        __syncwarp();
        if (first_ab) {
#pragma unroll
            for (int s = 0; s < NPRE; s++) {
                const uint32_t full = sb + B_FULL1 + 8 * s, dst = sb + s * R1_STAGE;
                e_expect_tma_2d(full, R1_STAGE, dst, &maps.x + ((tw >> 1) & 3), s * 64, a0 * 128);
                e_tma_2d(dst + 16384, &maps.x, s * 64, b0 * 256, full);
                e_tma_2d(dst + 32768, &maps.x, s * 64, b0 * 256 + 128, full);
            }
        } else {
#pragma unroll
            for (int s = 0; s < NPRE; s++) {
                const uint32_t full = sb + B_FULL1 + 8 * s, dst = sb + s * R1_STAGE;
                e_tma_3d(dst + 16384, &maps.wg, 0, s * 64, b0 * 2, full);
                e_tma_3d(dst + 32768, &maps.wu, 0, s * 64, b0 * 2, full);
                e_expect_tma_2d(full, R1_STAGE, dst, &maps.x, s * 64, a0 * 128);
            }
        }
        if (lane == 0) PROF_T(50);
    }
    const int rank = blockIdx.x & 1;
    const int G = (tw >> 12) & 31, jm = (tw >> 20) & 3;
    const bool is_main = G < 16;
    const int nrounds = is_main ? 2 : 4;
    const int m2 = 2 * (G & 7) + rank, nb = jm, kh = (G >> 3) & 1;
    const int wid = is_main ? m2 * 8 + kh * 4 + nb : 0;
    auto h_tile = [&](int r, int& m, int& ct) {
        if (!is_main) { m = a0 + 2 * r; ct = 11; }
        else if (r == 0) { m = a0; ct = b0; }
        else { m = m2; ct = 3 + kh * 4 + nb; }
    };
    const int ab_e = a0 + ((tw >> 2) & 1) * 5, ab_s = b0;
    const CUtensorMap* const mw = rank == 0 ? &maps.wg : &maps.wu;
    if (warp >= 8) {
        asm volatile("setmaxnreg.dec.sync.aligned.u32 40;");
        if (threadIdx.x == 288) {
            trap_if(sb & 1023);
            for (int s = NPRE; s < R1_N; s++) mbar_init(sb + B_FULL1 + 8 * s, 1);
            for (int s = 0; s < R1_N; s++) mbar_init(sb + B_EMPTY1 + 8 * s, 16);
            for (int s = 0; s < R2_N; s++) { mbar_init(sb + B_FULL2 + 8 * s, 1); mbar_init(sb + B_EMPTY2 + 8 * s, 16); }
            for (int s = 0; s < 4; s++) mbar_init(sb + B_STGF + 8 * s, 4);
            mbar_init(sb + B_STGE, 1);
            mbar_init(sb + B_DEP_AB, 1); mbar_init(sb + B_DEP_AB2, 1); mbar_init(sb + B_DEP_H, 1); mbar_init(sb + B_DEP_LATE, 1); mbar_init(sb + B_GRDY, 1);
            asm volatile("fence.mbarrier_init.release.cluster;" ::: "memory");
        }
        __syncwarp();
        cluster_arrive_relaxed();
        cluster_wait();
        if (warp == 8) {
            if (lane == 0) PROF_T(51);
            int it = NPRE;
            if (first_ab) {
                const CUtensorMap* ma = &maps.x + ((tw >> 1) & 3);
                const int arow = a0 * 128, brow = ab_s * 256 + rank * 128;
#pragma unroll 1
                for (; it < 10; it++) {
                    const int s = it & 3;
                    const uint32_t full = sb + B_FULL1 + 8 * s, dst = sb + s * R1_STAGE;
                    mbar_wait(sb + B_EMPTY1 + 8 * s, ((it >> 2) & 1) ^ 1);
                    e_expect_tma_2d(full, R1_STAGE, dst, ma, it * 64, arow);
                    e_tma_2d_mc(dst + 16384 + rank * 16384, &maps.x, it * 64, brow, full);
                }
            }
#pragma unroll 1
            for (int r = first_ab ? 1 : 0; r < nrounds; r++) {
                int m, ct;
                h_tile(r, m, ct);
#pragma unroll 1
                for (int kb = r == 0 ? NPRE : 0; kb < 10; kb++, it++) {
                    const int s = it & 3;
                    const uint32_t full = sb + B_FULL1 + 8 * s, dst = sb + s * R1_STAGE;
                    mbar_wait(sb + B_EMPTY1 + 8 * s, ((it >> 2) & 1) ^ 1);
                    e_expect_tma_2d(full, R1_STAGE, dst, &maps.x, kb * 64, m * 128);
                    e_tma_3d_mc(dst + 16384 + rank * 16384, mw, 0, kb * 64, ct * 2, full);
                }
            }
            if (is_main) {
                const CUtensorMap* mws = kh ? &maps.wsim : &maps.wsre;
                const int brow = kh * 640 + nb * 160 + rank * 80;
                const uint32_t boff = 16384 + rank * 10240;
#pragma unroll
                for (int kb = 0; kb < R2_N; kb++) {
                    const uint32_t full = sb + B_FULL2 + 8 * kb, dst = sb + kb * R2_STAGE;
                    const int kc = ((kb & 14) << 7) + ((kb & 1) << 6);
                    if (kb != 3) mbar_wait(sb + B_EMPTY1 + 8 * (kb == 4 ? 3 : kb), 0);
                    e_expect_tma_2d(full, R2_STAGE, dst, mws, kc, m2 * 128);
                    if (kb == 0) { if (lane == 0) PROF_T(32); mbar_wait(sb + B_DEP_AB, 0); if (lane == 0) PROF_T(33); }
                    e_tma_2d_mc(dst + boff, &maps.abT, kc, brow, full);
                }
                int s = 0, ph = 0;
#pragma unroll 1
                for (int kb = R2_N; kb < 32; kb++) {
                    const uint32_t full = sb + B_FULL2 + 8 * s, dst = sb + s * R2_STAGE;
                    const int kc = ((kb & 14) << 7) + ((kb >> 4) << 7) + ((kb & 1) << 6);
                    if (kb == 16) mbar_wait(sb + B_DEP_AB2, 0);
                    mbar_wait(sb + B_EMPTY2 + 8 * s, ph);
                    e_expect_tma_2d(full, R2_STAGE, dst, mws, kc, m2 * 128);
                    e_tma_2d_mc(dst + boff, &maps.abT, kc, brow, full);
                    if (++s == R2_N) { s = 0; ph ^= 1; }
                }
                mbar_wait(sb + B_DEP_H, 0);
#pragma unroll 1
                for (int kb = 0; kb < 12; kb++) {
                    const uint32_t full = sb + B_FULL2 + 8 * s, dst = sb + s * R2_STAGE;
                    const int kk = kh * 768 + kb * 64;
                    mbar_wait(sb + B_EMPTY2 + 8 * s, ph);
                    e_tma_3d_mc(dst + boff, &maps.wdown, 0, kk + rank * 32, nb * 5, full);
                    if (kb == 10 && kh) { if (lane == 0) PROF_T(36); mbar_wait(sb + B_DEP_LATE, 0); if (lane == 0) PROF_T(37); }
                    e_expect_tma_2d(full, R2_STAGE, dst, &maps.h, kk, m2 * 128);
                    if (++s == R2_N) { s = 0; ph ^= 1; }
                }
            }
        } else if (warp == 9) {
            if (lane < 13) prefetch_map(&maps.x + lane);
            if (lane == 0) {
                int q = 0;
                for (int r = 0; r < nrounds; r++) {
                    const bool ab = first_ab && r == 0;
                    int m, ct;
                    h_tile(r, m, ct);
                    for (int hb = 0; hb < (ab ? 2 : 1); hb++, q++) {
                        for (int p = 0; p < 4; p++) {
                            const int w = ab ? p >> 1 : p & 1, b = ab ? p & 1 : p >> 1;
                            mbar_wait(sb + B_STGF + 16 * w + 8 * b, q & 1);
                            if (r == 0 && p == 0) PROF_T(53 + hb * 2);
                            const uint32_t src = sb + STG_OFF + b * STG_SZ + w * 8192;
                            if (ab) tma_store_2d(&maps.abT_st, src, ab_s * 256 + hb * 128 + b * 64, ab_e * 128 + w * 64);
                            else tma_store_2d(&maps.h_st, src, ct * 128 + b * 64, m * 128 + w * 64);
                            bulk_commit();
                            if (r < 3) bulk_wait_read0();
                        }
                        mbar_arrive(sb + B_STGE);
                        if (r == 0) PROF_T(54 + hb * 2);
                        bulk_wait0();
                        flag_publish(ab ? &g_cnt[(hb ? 66 : 1) * 32] : (ct == 11 ? &g_cnt[(34 + m) * 32] : &g_cnt[(2 + m * 2 + (ct >= 6)) * 32]));
                        if (r == 0) PROF_T(46 + hb);
                    }
                    PROF_T(40 + r);
                }
            }
        } else if (warp == 10) {
            if (is_main) {
                const unsigned epoch1 = ld_relaxed(&g_cnt[0]) / NCTA + 1;
                if (lane == 0) {
                    flag_wait(&g_cnt[1 * 32], epoch1 * 80);
                    PROF_T(57);
                    fence_async_global();
                    mbar_arrive(sb + B_DEP_AB);
                    PROF_T(44);
                    flag_wait(&g_cnt[66 * 32], epoch1 * 80);
                    fence_async_global();
                    mbar_arrive(sb + B_DEP_AB2);
                    PROF_T(59);
                }
                if (lane == 0) {
                    flag_wait(&g_cnt[(2 + m2 * 2 + kh) * 32], epoch1 * (kh ? 5 : 6));
                    PROF_T(58);
                    fence_async_global();
                    mbar_arrive(sb + B_DEP_H);
                    PROF_T(45);
                }
                __syncwarp();
                flag_wait(&g_cnt[(50 + m2) * 32], epoch1 * 8);
                fence_async_global();
                float4 gv;
                asm volatile("ld.relaxed.gpu.global.v4.f32 {%0, %1, %2, %3}, [%4];" : "=f"(gv.x), "=f"(gv.y), "=f"(gv.z), "=f"(gv.w) : "l"(g_gate + m2 * 128 + lane * 4) : "memory");
                asm volatile("st.shared.v4.f32 [%0], {%1, %2, %3, %4};" ::"r"(sb + G_OFF + lane * 16), "f"(gv.x), "f"(gv.y), "f"(gv.z), "f"(gv.w) : "memory");
                __syncwarp();
                if (lane == 0) {
                    mbar_arrive(sb + B_GRDY);
                    if (kh) {
                        flag_wait(&g_cnt[(34 + m2) * 32], epoch1);
                        fence_async_global();
                        mbar_arrive(sb + B_DEP_LATE);
                        PROF_T(49);
                    }
                }
            }
        } else if (is_main) {
            uint4* op = reinterpret_cast<uint4*>(out + (size_t)wid * 16 * D_);
            mbar_wait(sb + B_FULL1 + 24, 0);
            if (lane == 0) PROF_T(19);
            const uint2* gw2 = reinterpret_cast<const uint2*>(gw);
            uint2 wv[5];
#pragma unroll
            for (int j = 0; j < 5; j++) wv[j] = __ldg(gw2 + j * 32 + lane);
            const CUtensorMap* mws = kh ? &maps.wsim : &maps.wsre;
#pragma unroll 1
            for (int i = 0; i < 8; i++) {
                const int row = wid * 16 + 2 * i;
                const uint2* xr = reinterpret_cast<const uint2*>(x + (size_t)row * D_);
                uint2 a[10];
#pragma unroll
                for (int j = 0; j < 10; j++) a[j] = __ldg(xr + j * 32 + lane);
                if (i < 4) {
#pragma unroll
                    for (int j = 0; j < 10; j++) op[(i * 10 + j) * 32 + lane] = make_uint4(0, 0, 0, 0);
                }
                float s0 = 0.f, s1 = 0.f;
#pragma unroll
                for (int j = 0; j < 5; j++) {
                    __nv_bfloat162 p;
                    uint32_t u;
                    p = __hmul2(*reinterpret_cast<__nv_bfloat162*>(&a[j].x), *reinterpret_cast<__nv_bfloat162*>(&wv[j].x)); u = *reinterpret_cast<uint32_t*>(&p); s0 += bf_lo(u) + bf_hi(u);
                    p = __hmul2(*reinterpret_cast<__nv_bfloat162*>(&a[j].y), *reinterpret_cast<__nv_bfloat162*>(&wv[j].y)); u = *reinterpret_cast<uint32_t*>(&p); s0 += bf_lo(u) + bf_hi(u);
                    p = __hmul2(*reinterpret_cast<__nv_bfloat162*>(&a[5 + j].x), *reinterpret_cast<__nv_bfloat162*>(&wv[j].x)); u = *reinterpret_cast<uint32_t*>(&p); s1 += bf_lo(u) + bf_hi(u);
                    p = __hmul2(*reinterpret_cast<__nv_bfloat162*>(&a[5 + j].y), *reinterpret_cast<__nv_bfloat162*>(&wv[j].y)); u = *reinterpret_cast<uint32_t*>(&p); s1 += bf_lo(u) + bf_hi(u);
                }
#pragma unroll
                for (int o = 16; o > 0; o >>= 1) { s0 += __shfl_xor_sync(0xffffffffu, s0, o); s1 += __shfl_xor_sync(0xffffffffu, s1, o); }
                if (lane < 2) {
                    float z = __bfloat162float(__float2bfloat16(lane ? s1 : s0));
                    g_gate[row + lane] = __bfloat162float(__float2bfloat16(__fdividef(1.0f, 1.0f + __expf(-z))));
                }
            }
            __syncwarp();
            if (lane == 0) {
                flag_publish(&g_cnt[(50 + m2) * 32]);
                PROF_T(48);
            }
        }
        __syncwarp();
        cluster_arrive_relaxed();
        cluster_wait();
    } else {
        cluster_arrive_relaxed();
        asm volatile("setmaxnreg.inc.sync.aligned.u32 232;");
        const int wg = warp >> 2;
        Ctx c;
        c.sb = sb;
        c.a_off = wg * 8192;
        c.d16 = (sb & 0x3FFFF) >> 4;
        c.on = gridDim.x != 0;
        asm volatile("" : "+r"(c.on));
        c.lane = lane;
        asm volatile("mapa.shared::cluster.u32 %0, %1, %2;" : "=r"(c.rel) : "r"(sb), "r"(lane & 1));
        c.st_addr = sb + STG_OFF + (warp * 16 + (lane & 7) + ((lane >> 3) & 1) * 8) * 128 + (((lane >> 4) ^ (lane & 7)) << 4);
        c.it1 = 0;
        c.q = 0;
        cluster_wait();
        uint32_t pk[64];
        {
            float acc[128];
            if (threadIdx.x == 0) PROF_T(0);
            if (first_ab) tile_plain<0>(acc, c); else tile_plain<1>(acc, c);
            finish_s1(acc, pk, c);
            if (threadIdx.x == 0) PROF_T(1);
            if (threadIdx.x == 128) PROF_T(5);
            bool prev_ab = first_ab;
#pragma unroll 1
            for (int r = 1; r < nrounds; r++) {
                s1_epi_iter<0>(acc, pk, c, prev_ab); s1_epi_iter<1>(acc, pk, c, prev_ab); s1_epi_iter<2>(acc, pk, c, prev_ab);
                s1_epi_iter<3>(acc, pk, c, prev_ab); s1_epi_iter<4>(acc, pk, c, prev_ab); s1_epi_iter<5>(acc, pk, c, prev_ab);
                s1_epi_iter<6>(acc, pk, c, prev_ab); s1_epi_iter<7>(acc, pk, c, prev_ab); s1_epi_iter<8>(acc, pk, c, prev_ab);
                s1_epi_iter<9>(acc, pk, c, prev_ab);
                finish_s1(acc, pk, c);
                prev_ab = false;
                if (threadIdx.x == 0) PROF_T(1 + r);
                if (threadIdx.x == 128 && r == 1) PROF_T(6);
            }
        }
        if (!is_main) {
            epi_h<0>(pk, c); epi_h<1>(pk, c); epi_h<2>(pk, c); epi_h<3>(pk, c);
            epi_h<4>(pk, c); epi_h<5>(pk, c); epi_h<6>(pk, c); epi_h<7>(pk, c);
        } else {
            float accY[80], accF[80];
            s2_epi_iter<0>(accY, pk, c); s2_epi_iter<1>(accY, pk, c); s2_epi_iter<2>(accY, pk, c); s2_epi_iter<3>(accY, pk, c);
            s2_epi_iter<4>(accY, pk, c); s2_epi_iter<5>(accY, pk, c); s2_epi_iter<6>(accY, pk, c); s2_epi_iter<7>(accY, pk, c);
            if (threadIdx.x == 0) PROF_T(8);
            s2_epi_iter<8>(accY, pk, c); s2_epi_iter<9>(accY, pk, c); s2_epi_iter<10>(accY, pk, c); s2_epi_iter<11>(accY, pk, c);
            s2_epi_iter<12>(accY, pk, c); s2_epi_iter<13>(accY, pk, c); s2_epi_iter<14>(accY, pk, c); s2_epi_iter<15>(accY, pk, c);
            s2_epi_iter<16>(accY, pk, c);
            int s = 17 % R2_N, ps = 16 % R2_N, ph = (17 / R2_N) & 1;
#pragma unroll 1
            for (int kb = 17; kb < 32; kb++) {
                mbar_wait(sb + B_FULL2 + 8 * s, ph);
                mma_s2<0>(accY, c, s, false);
                wgmma_wait<1>();
                release(c, B_EMPTY2 + 8 * ps);
                ps = s;
                if (++s == R2_N) { s = 0; ph ^= 1; }
            }
            if (threadIdx.x == 0) PROF_T(9);
#pragma unroll 1
            for (int kb = 32; kb < 44; kb++) {
                if (kb == 44 - LAG && wg == 1) asm volatile("bar.sync 1, 256;" ::: "memory");
                mbar_wait(sb + B_FULL2 + 8 * s, ph);
                mma_s2<1>(accF, c, s, kb == 32);
                if (kb == 43 && wg == 0) asm volatile("bar.arrive 1, 256;" ::: "memory");
                wgmma_wait<1>();
                if (kb < 40) release(c, B_EMPTY2 + 8 * ps);
                ps = s;
                if (++s == R2_N) { s = 0; ph ^= 1; }
            }
            mbar_wait(sb + B_GRDY, 0);
            float g0, g1;
            asm volatile("ld.shared.f32 %0, [%1];" : "=f"(g0) : "r"(sb + G_OFF + 4 * (warp * 16 + (lane >> 2))));
            asm volatile("ld.shared.f32 %0, [%1];" : "=f"(g1) : "r"(sb + G_OFF + 4 * (warp * 16 + (lane >> 2) + 8)));
            const float f0 = __bfloat162float(__float2bfloat16(1.0f - g0)), f1 = __bfloat162float(__float2bfloat16(1.0f - g1));
            if (kh) { g0 = -g0; g1 = -g1; }
#pragma unroll
            for (int i = 0; i < 80; i++) asm volatile("" : "+f"(accY[i])::"memory");
#pragma unroll
            for (int i = 0; i < 80; i++) accY[i] *= (i & 2) ? g1 : g0;
#pragma unroll
            for (int i = 0; i < 80; i++) asm volatile("" : "+f"(accY[i])::"memory");
            wgmma_wait<0>();
#pragma unroll
            for (int i = 0; i < 80; i++) asm volatile("" : "+f"(accF[i])::"memory");
            if ((threadIdx.x & 127) == 0) PROF_T(10 + wg);
            const uint32_t ob = sb + OUT_OFF + warp * 5120;
            const uint32_t row = (lane & 7) + ((lane >> 3) & 1) * 8;
#pragma unroll
            for (int p = 0; p < 10; p++) {
                uint32_t o[4];
#pragma unroll
                for (int j = 0; j < 4; j++) {
                    const int i = 8 * p + 2 * j;
                    const float f = (j & 1) ? f1 : f0;
                    o[j] = pack_bf16(fmaf(f, accF[i], accY[i]), fmaf(f, accF[i + 1], accY[i + 1]));
                }
                const uint32_t cg = (p & 1) * 2 + (lane >> 4);
                stmatrix_x4(ob + (p >> 1) * 1024 + row * 64 + ((cg ^ ((row >> 1) & 3)) << 4), o[0], o[1], o[2], o[3]);
            }
            fence_async_smem();
            __syncwarp();
            if (lane == 0) {
                tma_reduce_add_3d(&maps.out, ob, 0, m2 * 128 + warp * 16, nb * 5);
                bulk_commit();
                if ((threadIdx.x & 127) == 0) PROF_T(12 + wg);
                bulk_wait_read0();
            }
            if ((threadIdx.x & 127) == 0) PROF_T(14 + wg);
        }
        __syncwarp();
        cluster_arrive_relaxed();
        cluster_wait();
        if (threadIdx.x == 0) {
            atomicAdd(&g_cnt[0], 1u);
            PROF_T(16);
        }
    }
}

typedef CUresult (*EncodeFn)(CUtensorMap*, CUtensorMapDataType, cuuint32_t, void*, const cuuint64_t*, const cuuint64_t*, const cuuint32_t*,
                             const cuuint32_t*, CUtensorMapInterleave, CUtensorMapSwizzle, CUtensorMapL2promotion, CUtensorMapFloatOOBfill);

static void enc(EncodeFn fn, CUtensorMap* m, const void* ptr, int rank, cuuint64_t d0, cuuint64_t d1, cuuint64_t d2, cuuint64_t s1, cuuint64_t s2,
                cuuint32_t b0, cuuint32_t b1, cuuint32_t b2, CUtensorMapSwizzle swz) {
    cuuint64_t dims[3] = {d0, d1, d2}, strides[2] = {s1, s2};
    cuuint32_t box[3] = {b0, b1, b2}, es[3] = {1, 1, 1};
    fn(m, CU_TENSOR_MAP_DATA_TYPE_BFLOAT16, rank, const_cast<void*>(ptr), dims, strides, box, es, CU_TENSOR_MAP_INTERLEAVE_NONE, swz,
       PROMO, CU_TENSOR_MAP_FLOAT_OOB_FILL_NONE);
}

extern "C" void kernel_launch(void* const* d_in, const int* in_sizes, int n_in, void* d_out, int out_size) {
    (void)in_sizes; (void)n_in; (void)out_size;
    const bf16* x = (const bf16*)d_in[0];
    const bf16* wsre = (const bf16*)d_in[1];
    const bf16* wsim = (const bf16*)d_in[2];
    const bf16* wdre = (const bf16*)d_in[3];
    const bf16* wdim = (const bf16*)d_in[4];
    const bf16* wg = (const bf16*)d_in[6];
    const bf16* wu = (const bf16*)d_in[7];
    const bf16* wdown = (const bf16*)d_in[8];
    const bf16* gw = (const bf16*)d_in[9];

    void* fnp = nullptr;
    cudaDriverEntryPointQueryResult qr;
    cudaGetDriverEntryPoint("cuTensorMapEncodeTiled", &fnp, cudaEnableDefault, &qr);
    EncodeFn fn = (EncodeFn)fnp;
    void *abT, *H;
    cudaGetSymbolAddress(&abT, g_abT);
    cudaGetSymbolAddress(&H, g_H);

    Maps mp;
    const CUtensorMapSwizzle S128 = CU_TENSOR_MAP_SWIZZLE_128B, S64 = CU_TENSOR_MAP_SWIZZLE_64B;
    enc(fn, &mp.x, x, 2, D_, S_, 1, D_ * 2, 0, 64, 128, 1, S128);
    enc(fn, &mp.wdre, wdre, 2, D_, D_, 1, D_ * 2, 0, 64, 128, 1, S128);
    enc(fn, &mp.wdim, wdim, 2, D_, D_, 1, D_ * 2, 0, 64, 128, 1, S128);
    enc(fn, &mp.wg, wg, 3, 64, D_, F_ / 64, F_ * 2, 128, 64, 64, 2, S128);
    enc(fn, &mp.wu, wu, 3, 64, D_, F_ / 64, F_ * 2, 128, 64, 64, 2, S128);
    enc(fn, &mp.wsre, wsre, 2, S_, S_, 1, S_ * 2, 0, 64, 128, 1, S128);
    enc(fn, &mp.wsim, wsim, 2, S_, S_, 1, S_ * 2, 0, 64, 128, 1, S128);
    enc(fn, &mp.abT, abT, 2, S_, 2 * D_, 1, S_ * 2, 0, 64, 80, 1, S128);
    enc(fn, &mp.abT_st, abT, 2, S_, 2 * D_, 1, S_ * 2, 0, 64, 64, 1, S128);
    enc(fn, &mp.h_st, H, 2, F_, S_, 1, F_ * 2, 0, 64, 64, 1, S128);
    enc(fn, &mp.h, H, 2, F_, S_, 1, F_ * 2, 0, 64, 128, 1, S128);
    enc(fn, &mp.wdown, wdown, 3, 32, F_, D_ / 32, D_ * 2, 64, 32, 32, 5, S64);
    enc(fn, &mp.out, d_out, 3, 32, S_, D_ / 32, D_ * 2, 64, 32, 16, 5, S64);

    for (int b = 0; b < NCTA; b++) {
        const int c = b >> 1, t = c - 4, rank = b & 1;
        int G, j;
        if (t < 0) { G = 15; j = c; }
        else if (t < 32) { const int v = t & 7; G = v == 0 ? 14 : 2 * (v - 1); j = t >> 3; }
        else if (t < 60) { G = 2 * ((t - 32) % 7) + 1; j = (t - 32) / 7; }
        else { G = 16; j = t - 60; }
        uint32_t ab = 0, mapsel = 0, a0, b0;
        if (G < 10) {
            const int e = 2 * (G % 5) + rank;
            ab = 1; mapsel = e < 5 ? 1 : 2; a0 = e % 5; b0 = (G / 5) * 4 + j;
        } else if (G < 16) {
            const int i = (G - 10) * 4 + j;
            a0 = 2 * (i / 3) + rank; b0 = i % 3;
        } else {
            a0 = 8 * j + rank; b0 = 11;
        }
        mp.tab[b] = ab | (mapsel << 1) | (a0 << 4) | (b0 << 8) | (G << 12) | (j << 20);
    }
    cudaFuncSetAttribute(fused_kernel, cudaFuncAttributeMaxDynamicSharedMemorySize, SMEM_BYTES);
    fused_kernel<<<NCTA, 384, SMEM_BYTES>>>(mp, x, gw, wdown, (bf16*)d_out);
}
```

```cpp
#include <cuda_runtime.h>
#include <cuda_bf16.h>
#include <cuda.h>
#include <stdint.h>

typedef __nv_bfloat16 bf16;

constexpr int S_ = 2048, D_ = 640, F_ = 1536;
constexpr int NCTA = 132;
constexpr int STAG = 2;
constexpr int TLAG = 1;
constexpr int AB2_ITER = 4;

__device__ __align__(1024) bf16 g_abT[2 * D_ * S_];
__device__ __align__(1024) bf16 g_H[S_ * F_];
__device__ __align__(128) float g_gate[S_];
__device__ __align__(128) unsigned long long g_ticket;
__device__ __align__(128) unsigned g_cnt[80 * 32];

struct Maps {
    uint32_t tab[144];
    CUtensorMap x, wdre, wdim, wg, wu, wsre, wsim, abT, abT_st, h, h_st, wdown, out, out64;
};

constexpr int R1_STAGE = 49152;
constexpr int R2_STAGE = 36864, R2_N = 5;
constexpr int STG_OFF = 196608, STG_SZ = 16384;
constexpr int SLOTX_OFF = 184320;
constexpr int OUT0_OFF = 221184;
constexpr int BAR_OFF = 229376;
constexpr int B_FULL1 = BAR_OFF, B_EMPTY1 = BAR_OFF + 32, B_EMPTY2 = BAR_OFF + 64, B_STGF = BAR_OFF + 128  , B_FREEX = BAR_OFF + 160;
constexpr int B_FULL2 = BAR_OFF + 192, B_FULLX = BAR_OFF + 232, B_STGE = BAR_OFF + 240, B_DEP_AB = BAR_OFF + 248, B_DEP_AB2 = BAR_OFF + 256;
constexpr int B_DEP_H = BAR_OFF + 264, B_DEP_LATE = BAR_OFF + 272, B_GRDY = BAR_OFF + 280;
constexpr unsigned long long BAR_LOG2_COUNT = 0x124440;
constexpr int G_OFF = BAR_OFF + 384;
constexpr int SMEM_BYTES = BAR_OFF + 1280;

__device__ __forceinline__ void trap_if(uint32_t cond) { asm volatile("{\n.reg .pred p;\nsetp.ne.u32 p, %0, 0;\n@p trap;\n}" ::"r"(cond)); }
__device__ __forceinline__ uint32_t smem_u32(const void* p) { return (uint32_t)__cvta_generic_to_shared(p); }
__device__ __forceinline__ void mbar_init(uint32_t bar, int count) { asm volatile("mbarrier.init.shared::cta.b64 [%0], %1;" ::"r"(bar), "r"(count)); }
__device__ __forceinline__ void mbar_arrive(uint32_t bar) { asm volatile("mbarrier.arrive.shared::cta.b64 _, [%0];" ::"r"(bar) : "memory"); }
__device__ __forceinline__ void mbar_arrive_cluster(uint32_t bar, uint32_t cta) {
    asm volatile("{\n.reg .b32 ra;\nmapa.shared::cluster.u32 ra, %0, %1;\nmbarrier.arrive.shared::cluster.b64 _, [ra];\n}" ::"r"(bar), "r"(cta) : "memory");
}
__device__ __forceinline__ void mbar_wait(uint32_t bar, uint32_t parity) {
    asm volatile(
        "{\n.reg .pred p;\n.reg .u32 n;\nmov.u32 n, 0;\nLAB_WAIT:\n"
        "mbarrier.try_wait.parity.shared::cta.b64 p, [%0], %1;\n@p bra DONE;\n"
        "add.u32 n, n, 1;\nsetp.lt.u32 p, n, 1048576;\n@p bra LAB_WAIT;\ntrap;\nDONE:\n}" ::"r"(bar), "r"(parity) : "memory");
}
__device__ __forceinline__ void flag_wait(const unsigned* p, unsigned target) {
    asm volatile(
        "{\n.reg .pred p;\n.reg .u32 n, v;\n.reg .s32 d;\nmov.u32 n, 0;\nLAB_WAIT:\n"
        "ld.acquire.gpu.global.u32 v, [%0];\nsub.s32 d, v, %1;\nsetp.ge.s32 p, d, 0;\n@p bra DONE;\n"
        "add.u32 n, n, 1;\nsetp.lt.u32 p, n, 4194304;\n@p bra LAB_WAIT;\ntrap;\nDONE:\n}" ::"l"(p), "r"(target) : "memory");
}
__device__ __forceinline__ void fence_async_global() { asm volatile("fence.proxy.async.global;" ::: "memory"); }
__device__ __forceinline__ void e_expect_tma_2d(uint32_t bar, uint32_t bytes, uint32_t dst, const CUtensorMap* tm, int c0, int c1) {
    asm volatile("{\n.reg .pred p;\nelect.sync _|p, 0xffffffff;\n"
        "@p mbarrier.arrive.expect_tx.shared::cta.b64 _, [%2], %5;\n"
        "@p cp.async.bulk.tensor.2d.shared::cluster.global.mbarrier::complete_tx::bytes [%0], [%1, {%3, %4}], [%2];\n}"
        ::"r"(dst), "l"(tm), "r"(bar), "r"(c0), "r"(c1), "r"(bytes) : "memory");
}
__device__ __forceinline__ void e_tma_2d(uint32_t dst, const CUtensorMap* tm, int c0, int c1, uint32_t bar) {
    asm volatile("{\n.reg .pred p;\nelect.sync _|p, 0xffffffff;\n"
        "@p cp.async.bulk.tensor.2d.shared::cluster.global.mbarrier::complete_tx::bytes [%0], [%1, {%3, %4}], [%2];\n}"
        ::"r"(dst), "l"(tm), "r"(bar), "r"(c0), "r"(c1) : "memory");
}
__device__ __forceinline__ void e_tma_3d(uint32_t dst, const CUtensorMap* tm, int c0, int c1, int c2, uint32_t bar) {
    asm volatile("{\n.reg .pred p;\nelect.sync _|p, 0xffffffff;\n"
        "@p cp.async.bulk.tensor.3d.shared::cluster.global.mbarrier::complete_tx::bytes [%0], [%1, {%3, %4, %5}], [%2];\n}"
        ::"r"(dst), "l"(tm), "r"(bar), "r"(c0), "r"(c1), "r"(c2) : "memory");
}
__device__ __forceinline__ void e_reduce_add_3d(const CUtensorMap* tm, uint32_t src, int c0, int c1, int c2) {
    asm volatile("{\n.reg .pred p;\nelect.sync _|p, 0xffffffff;\n"
        "@p cp.reduce.async.bulk.tensor.3d.global.shared::cta.add.tile.bulk_group [%0, {%2, %3, %4}], [%1];\n}"
        ::"l"(tm), "r"(src), "r"(c0), "r"(c1), "r"(c2) : "memory");
}
__device__ __forceinline__ void e_reduce_add_2d(const CUtensorMap* tm, uint32_t src, int c0, int c1) {
    asm volatile("{\n.reg .pred p;\nelect.sync _|p, 0xffffffff;\n"
        "@p cp.reduce.async.bulk.tensor.2d.global.shared::cta.add.tile.bulk_group [%0, {%2, %3}], [%1];\n}"
        ::"l"(tm), "r"(src), "r"(c0), "r"(c1) : "memory");
}
__device__ __forceinline__ uint64_t policy_evict_first() {
    uint64_t p;
    asm volatile("createpolicy.fractional.L2::evict_first.b64 %0, 1.0;" : "=l"(p));
    return p;
}
__device__ __forceinline__ void e_expect_tma_2d_hint(uint32_t bar, uint32_t bytes, uint32_t dst, const CUtensorMap* tm, int c0, int c1, uint64_t pol) {
    asm volatile("{\n.reg .pred p;\nelect.sync _|p, 0xffffffff;\n"
        "@p mbarrier.arrive.expect_tx.shared::cta.b64 _, [%2], %5;\n"
        "@p cp.async.bulk.tensor.2d.shared::cluster.global.mbarrier::complete_tx::bytes.L2::cache_hint [%0], [%1, {%3, %4}], [%2], %6;\n}"
        ::"r"(dst), "l"(tm), "r"(bar), "r"(c0), "r"(c1), "r"(bytes), "l"(pol) : "memory");
}
__device__ __forceinline__ void e_prefetch_2d_hint(const CUtensorMap* tm, int c0, int c1, uint64_t pol) {
    asm volatile("{\n.reg .pred p;\nelect.sync _|p, 0xffffffff;\n@p cp.async.bulk.prefetch.tensor.2d.L2.global.L2::cache_hint [%0, {%1, %2}], %3;\n}" ::"l"(tm), "r"(c0), "r"(c1), "l"(pol) : "memory");
}
__device__ __forceinline__ void e_prefetch_3d(const CUtensorMap* tm, int c0, int c1, int c2) {
    asm volatile("{\n.reg .pred p;\nelect.sync _|p, 0xffffffff;\n@p cp.async.bulk.prefetch.tensor.3d.L2.global [%0, {%1, %2, %3}];\n}" ::"l"(tm), "r"(c0), "r"(c1), "r"(c2) : "memory");
}
__device__ __forceinline__ void e_tma_2d_mc(uint32_t dst, const CUtensorMap* tm, int c0, int c1, uint32_t bar) {
    asm volatile("{\n.reg .pred p;\nelect.sync _|p, 0xffffffff;\n"
        "@p cp.async.bulk.tensor.2d.shared::cluster.global.mbarrier::complete_tx::bytes.multicast::cluster [%0], [%1, {%3, %4}], [%2], %5;\n}"
        ::"r"(dst), "l"(tm), "r"(bar), "r"(c0), "r"(c1), "h"((uint16_t)3) : "memory");
}
__device__ __forceinline__ void e_tma_3d_mc(uint32_t dst, const CUtensorMap* tm, int c0, int c1, int c2, uint32_t bar) {
    asm volatile("{\n.reg .pred p;\nelect.sync _|p, 0xffffffff;\n"
        "@p cp.async.bulk.tensor.3d.shared::cluster.global.mbarrier::complete_tx::bytes.multicast::cluster [%0], [%1, {%3, %4, %5}], [%2], %6;\n}"
        ::"r"(dst), "l"(tm), "r"(bar), "r"(c0), "r"(c1), "r"(c2), "h"((uint16_t)3) : "memory");
}
__device__ __forceinline__ void tma_store_2d(const CUtensorMap* tm, uint32_t src, int c0, int c1) {
    asm volatile("cp.async.bulk.tensor.2d.global.shared::cta.bulk_group [%0, {%2, %3}], [%1];" ::"l"(tm), "r"(src), "r"(c0), "r"(c1) : "memory");
}
__device__ __forceinline__ void flag_publish(unsigned* f) {
    asm volatile("fence.acq_rel.gpu;\nred.relaxed.gpu.global.add.u32 [%0], 1;" ::"l"(f) : "memory");
}
__device__ __forceinline__ void prefetch_map(const CUtensorMap* tm) { asm volatile("prefetch.tensormap [%0];" ::"l"(tm) : "memory"); }
__device__ __forceinline__ void bulk_commit() { asm volatile("cp.async.bulk.commit_group;" ::: "memory"); }
__device__ __forceinline__ void bulk_wait_read0() { asm volatile("cp.async.bulk.wait_group.read 0;" ::: "memory"); }
__device__ __forceinline__ void bulk_wait0() { asm volatile("cp.async.bulk.wait_group 0;" ::: "memory"); }
__device__ __forceinline__ void fence_async_smem() { asm volatile("fence.proxy.async.shared::cta;" ::: "memory"); }
__device__ __forceinline__ void wgmma_fence() { asm volatile("wgmma.fence.sync.aligned;" ::: "memory"); }
__device__ __forceinline__ void wgmma_commit() { asm volatile("wgmma.commit_group.sync.aligned;" ::: "memory"); }
template <int N> __device__ __forceinline__ void wgmma_wait() { asm volatile("wgmma.wait_group.sync.aligned %0;" ::"n"(N) : "memory"); }
__device__ __forceinline__ void cluster_arrive_relaxed() { asm volatile("barrier.cluster.arrive.relaxed.aligned;" ::: "memory"); }
__device__ __forceinline__ void cluster_wait() { asm volatile("barrier.cluster.wait.acquire.aligned;" ::: "memory"); }
__device__ __forceinline__ uint64_t mk_desc(uint32_t lo, uint32_t hi) {
    uint64_t d;
    asm("mov.b64 %0, {%1, %2};" : "=l"(d) : "r"(lo), "r"(hi));
    return d;
}
__device__ __forceinline__ void stmatrix_x4(uint32_t addr, uint32_t r0, uint32_t r1, uint32_t r2, uint32_t r3) {
    asm volatile("stmatrix.sync.aligned.m8n8.x4.shared.b16 [%0], {%1, %2, %3, %4};" ::"r"(addr), "r"(r0), "r"(r1), "r"(r2), "r"(r3) : "memory");
}
__device__ __forceinline__ uint32_t pack_bf16(float lo, float hi) {
    uint32_t r;
    asm("cvt.rn.bf16x2.f32 %0, %1, %2;" : "=r"(r) : "f"(hi), "f"(lo));
    return r;
}
__device__ __forceinline__ float bf_lo(uint32_t v) { return __uint_as_float(v << 16); }
__device__ __forceinline__ float bf_hi(uint32_t v) { return __uint_as_float(v & 0xffff0000u); }
__device__ __forceinline__ float geglu(float x, float u) {
    float z = fmaf(x * x, 0.7978845608028654f * 0.044715f, 0.7978845608028654f) * x, th;
    asm("tanh.approx.f32 %0, %1;" : "=f"(th) : "f"(z));
    const float hp = (0.5f * x) * u;
    return fmaf(hp, th, hp);
}
__device__ __forceinline__ uint32_t geglu2(uint32_t g, uint32_t u) { return pack_bf16(geglu(bf_lo(g), bf_lo(u)), geglu(bf_hi(g), bf_hi(u))); }

template <int TB>
__device__ __forceinline__ void wgmma_n256(float (&d)[128], uint64_t da, uint64_t db, int scale_d) {
    asm volatile(
        "{\n.reg .pred p;\nsetp.ne.b32 p, %130, 0;\n"
        "wgmma.mma_async.sync.aligned.m64n256k16.f32.bf16.bf16 {"
        "%0, %1, %2, %3, %4, %5, %6, %7, %8, %9, %10, %11, %12, %13, %14, %15, %16, %17, %18, %19, %20, %21, %22, %23, %24, %25, %26, %27, %28, %29, %30, %31, "
        "%32, %33, %34, %35, %36, %37, %38, %39, %40, %41, %42, %43, %44, %45, %46, %47, %48, %49, %50, %51, %52, %53, %54, %55, %56, %57, %58, %59, %60, %61, "
        "%62, %63, %64, %65, %66, %67, %68, %69, %70, %71, %72, %73, %74, %75, %76, %77, %78, %79, %80, %81, %82, %83, %84, %85, %86, %87, %88, %89, %90, %91, "
        "%92, %93, %94, %95, %96, %97, %98, %99, %100, %101, %102, %103, %104, %105, %106, %107, %108, %109, %110, %111, %112, %113, %114, %115, %116, %117, "
        "%118, %119, %120, %121, %122, %123, %124, %125, %126, %127"
        "}, %128, %129, p, 1, 1, 0, %131;\n}\n"
        : "+f"(d[0]), "+f"(d[1]), "+f"(d[2]), "+f"(d[3]), "+f"(d[4]), "+f"(d[5]), "+f"(d[6]), "+f"(d[7]), "+f"(d[8]), "+f"(d[9]), "+f"(d[10]), "+f"(d[11]),
          "+f"(d[12]), "+f"(d[13]), "+f"(d[14]), "+f"(d[15]), "+f"(d[16]), "+f"(d[17]), "+f"(d[18]), "+f"(d[19]), "+f"(d[20]), "+f"(d[21]), "+f"(d[22]),
          "+f"(d[23]), "+f"(d[24]), "+f"(d[25]), "+f"(d[26]), "+f"(d[27]), "+f"(d[28]), "+f"(d[29]), "+f"(d[30]), "+f"(d[31]), "+f"(d[32]), "+f"(d[33]),
          "+f"(d[34]), "+f"(d[35]), "+f"(d[36]), "+f"(d[37]), "+f"(d[38]), "+f"(d[39]), "+f"(d[40]), "+f"(d[41]), "+f"(d[42]), "+f"(d[43]), "+f"(d[44]),
          "+f"(d[45]), "+f"(d[46]), "+f"(d[47]), "+f"(d[48]), "+f"(d[49]), "+f"(d[50]), "+f"(d[51]), "+f"(d[52]), "+f"(d[53]), "+f"(d[54]), "+f"(d[55]),
          "+f"(d[56]), "+f"(d[57]), "+f"(d[58]), "+f"(d[59]), "+f"(d[60]), "+f"(d[61]), "+f"(d[62]), "+f"(d[63]), "+f"(d[64]), "+f"(d[65]), "+f"(d[66]),
          "+f"(d[67]), "+f"(d[68]), "+f"(d[69]), "+f"(d[70]), "+f"(d[71]), "+f"(d[72]), "+f"(d[73]), "+f"(d[74]), "+f"(d[75]), "+f"(d[76]), "+f"(d[77]),
          "+f"(d[78]), "+f"(d[79]), "+f"(d[80]), "+f"(d[81]), "+f"(d[82]), "+f"(d[83]), "+f"(d[84]), "+f"(d[85]), "+f"(d[86]), "+f"(d[87]), "+f"(d[88]),
          "+f"(d[89]), "+f"(d[90]), "+f"(d[91]), "+f"(d[92]), "+f"(d[93]), "+f"(d[94]), "+f"(d[95]), "+f"(d[96]), "+f"(d[97]), "+f"(d[98]), "+f"(d[99]),
          "+f"(d[100]), "+f"(d[101]), "+f"(d[102]), "+f"(d[103]), "+f"(d[104]), "+f"(d[105]), "+f"(d[106]), "+f"(d[107]), "+f"(d[108]), "+f"(d[109]),
          "+f"(d[110]), "+f"(d[111]), "+f"(d[112]), "+f"(d[113]), "+f"(d[114]), "+f"(d[115]), "+f"(d[116]), "+f"(d[117]), "+f"(d[118]), "+f"(d[119]),
          "+f"(d[120]), "+f"(d[121]), "+f"(d[122]), "+f"(d[123]), "+f"(d[124]), "+f"(d[125]), "+f"(d[126]), "+f"(d[127])
        : "l"(da), "l"(db), "r"(scale_d), "n"(TB));
}
template <int TB>
__device__ __forceinline__ void wgmma_n160(float (&d)[80], uint64_t da, uint64_t db, int scale_d) {
    asm volatile(
        "{\n.reg .pred p;\nsetp.ne.b32 p, %82, 0;\n"
        "wgmma.mma_async.sync.aligned.m64n160k16.f32.bf16.bf16 {"
        "%0, %1, %2, %3, %4, %5, %6, %7, %8, %9, %10, %11, %12, %13, %14, %15, %16, %17, %18, %19, %20, %21, %22, %23, %24, %25, %26, %27, %28, %29, %30, %31, "
        "%32, %33, %34, %35, %36, %37, %38, %39, %40, %41, %42, %43, %44, %45, %46, %47, %48, %49, %50, %51, %52, %53, %54, %55, %56, %57, %58, %59, %60, %61, "
        "%62, %63, %64, %65, %66, %67, %68, %69, %70, %71, %72, %73, %74, %75, %76, %77, %78, %79"
        "}, %80, %81, p, 1, 1, 0, %83;\n}\n"
        : "+f"(d[0]), "+f"(d[1]), "+f"(d[2]), "+f"(d[3]), "+f"(d[4]), "+f"(d[5]), "+f"(d[6]), "+f"(d[7]), "+f"(d[8]), "+f"(d[9]), "+f"(d[10]), "+f"(d[11]),
          "+f"(d[12]), "+f"(d[13]), "+f"(d[14]), "+f"(d[15]), "+f"(d[16]), "+f"(d[17]), "+f"(d[18]), "+f"(d[19]), "+f"(d[20]), "+f"(d[21]), "+f"(d[22]),
          "+f"(d[23]), "+f"(d[24]), "+f"(d[25]), "+f"(d[26]), "+f"(d[27]), "+f"(d[28]), "+f"(d[29]), "+f"(d[30]), "+f"(d[31]), "+f"(d[32]), "+f"(d[33]),
          "+f"(d[34]), "+f"(d[35]), "+f"(d[36]), "+f"(d[37]), "+f"(d[38]), "+f"(d[39]), "+f"(d[40]), "+f"(d[41]), "+f"(d[42]), "+f"(d[43]), "+f"(d[44]),
          "+f"(d[45]), "+f"(d[46]), "+f"(d[47]), "+f"(d[48]), "+f"(d[49]), "+f"(d[50]), "+f"(d[51]), "+f"(d[52]), "+f"(d[53]), "+f"(d[54]), "+f"(d[55]),
          "+f"(d[56]), "+f"(d[57]), "+f"(d[58]), "+f"(d[59]), "+f"(d[60]), "+f"(d[61]), "+f"(d[62]), "+f"(d[63]), "+f"(d[64]), "+f"(d[65]), "+f"(d[66]),
          "+f"(d[67]), "+f"(d[68]), "+f"(d[69]), "+f"(d[70]), "+f"(d[71]), "+f"(d[72]), "+f"(d[73]), "+f"(d[74]), "+f"(d[75]), "+f"(d[76]), "+f"(d[77]),
          "+f"(d[78]), "+f"(d[79])
        : "l"(da), "l"(db), "r"(scale_d), "n"(TB));
}


constexpr uint32_t DH_128 = (1024 >> 4) | (1u << 30);
constexpr uint32_t DH_64 = (512 >> 4) | (2u << 30);
constexpr uint32_t DL_K = 1u << 16;
constexpr uint32_t DL_N128 = (8192u >> 4) << 16;
constexpr uint32_t DL_N64 = (2048u >> 4) << 16;

struct Ctx {
    uint32_t sb;
    uint32_t a_off;
    uint32_t d16;
    uint32_t on;
    uint32_t st_addr;
    uint32_t lane;
    uint32_t rel;
    int it1;
    int q;
};

__device__ __forceinline__ void release(const Ctx& c, uint32_t off) {
    if (c.lane < 2) asm volatile("mbarrier.arrive.shared::cluster.b64 _, [%0];" ::"r"(c.rel + off) : "memory");
}

template <int TB>
__device__ __forceinline__ void mma_s1(float (&acc)[128], const Ctx& c, int s, bool first) {
    const uint32_t lb = c.d16 + s * (R1_STAGE >> 4) + (16384 >> 4) + (TB ? DL_N128 : DL_K);
    const uint32_t la = c.d16 + s * (R1_STAGE >> 4) + (c.a_off >> 4) + DL_K;
    wgmma_fence();
#pragma unroll
    for (int k = 0; k < 4; k++)
        wgmma_n256<TB>(acc, mk_desc(la + k * 2, DH_128), mk_desc(lb + k * (TB ? 128 : 2), DH_128), (k == 0 && first) ? 0 : 1);
    wgmma_commit();
}
template <int TB>
__device__ __forceinline__ void mma_s2(float (&acc)[80], const Ctx& c, int s, bool first) {
    const uint32_t lb = c.d16 + s * (R2_STAGE >> 4) + (16384 >> 4) + (TB ? DL_N64 : DL_K);
    const uint32_t la = c.d16 + s * (R2_STAGE >> 4) + (c.a_off >> 4) + DL_K;
    wgmma_fence();
#pragma unroll
    for (int k = 0; k < 4; k++)
        wgmma_n160<TB>(acc, mk_desc(la + k * 2, DH_128), TB ? mk_desc(lb + (k >> 1) * 640 + (k & 1) * 64, DH_64) : mk_desc(lb + k * 2, DH_128),
                       (k == 0 && first) ? 0 : 1);
    wgmma_commit();
}

__device__ __forceinline__ void stg_acquire(const Ctx& c) { mbar_wait(c.sb + B_STGE, (c.q & 1) ^ 1); }
__device__ __forceinline__ void stg_publish(const Ctx& c, int b) {
    fence_async_smem();
    __syncwarp();
    if (c.lane == 0) mbar_arrive(c.sb + B_STGF + (c.a_off >> 9) + 8 * b);
}
__device__ __forceinline__ void stg_store(const Ctx& c, int b, int p, uint32_t r0, uint32_t r1, uint32_t r2, uint32_t r3) {
    uint32_t a = c.st_addr;
    asm volatile("xor.b32 %0, %0, %1;" : "+r"(a) : "r"(p << 5));
    stmatrix_x4(a + b * STG_SZ, r0, r1, r2, r3);
}
template <int I>
__device__ __forceinline__ void epi_h(uint32_t (&pk)[64], Ctx& c) {
    if (I == 0) stg_acquire(c);
#pragma unroll
    for (int j = 0; j < 4; j++) asm volatile("" : "+r"(pk[4 * I + j]), "+r"(pk[32 + 4 * I + j]));
    uint32_t r0 = geglu2(pk[4 * I + 0], pk[32 + 4 * I + 0]);
    uint32_t r1 = geglu2(pk[4 * I + 1], pk[32 + 4 * I + 1]);
    uint32_t r2 = geglu2(pk[4 * I + 2], pk[32 + 4 * I + 2]);
    uint32_t r3 = geglu2(pk[4 * I + 3], pk[32 + 4 * I + 3]);
    stg_store(c, I >> 2, I & 3, r0, r1, r2, r3);
    if (I == 3 || I == 7) stg_publish(c, I >> 2);
    if (I == 7) c.q++;
}
template <int J>
__device__ __forceinline__ void epi_h_half(uint32_t (&pk)[64], Ctx& c) {
    if (J == 0) stg_acquire(c);
    pk[2 * J] = geglu2(pk[2 * J], pk[32 + 2 * J]);
    pk[2 * J + 1] = geglu2(pk[2 * J + 1], pk[32 + 2 * J + 1]);
    if (J & 1) {
        constexpr int I = J >> 1;
        stg_store(c, I >> 2, I & 3, pk[4 * I], pk[4 * I + 1], pk[4 * I + 2], pk[4 * I + 3]);
        if (I == 3 || I == 7) stg_publish(c, I >> 2);
    } else {
        asm volatile("" : "+r"(pk[2 * J]), "+r"(pk[2 * J + 1]));
    }
}
template <int H>
__device__ __forceinline__ void epi_ab(uint32_t (&pk)[64], Ctx& c) {
    stg_acquire(c);
#pragma unroll
    for (int b = 0; b < 2; b++) {
#pragma unroll
        for (int p = 0; p < 4; p++) {
            const int i = 32 * H + 16 * b + 4 * p;
            stg_store(c, b, p, pk[i], pk[i + 1], pk[i + 2], pk[i + 3]);
        }
    }
    fence_async_smem();
    __syncwarp();
    if (c.lane < 2) mbar_arrive(c.sb + B_STGF + (c.a_off >> 9) + 8 * c.lane);
    c.q++;
}
template <int I>
__device__ __forceinline__ void epi_step(uint32_t (&pk)[64], Ctx& c, bool prev_ab) {
    if (prev_ab) {
        if (I == 0) epi_ab<0>(pk, c);
        if (I == AB2_ITER) epi_ab<1>(pk, c);
    } else {
        if (I < 8) epi_h<(I < 8 ? I : 0)>(pk, c);
    }
}
__device__ __forceinline__ void finish_s1(float (&acc)[128], uint32_t (&pk)[64], Ctx& c) {
    wgmma_wait<0>();
    release(c, B_EMPTY1 + 8 * ((c.it1 - 1) & 3));
#pragma unroll
    for (int i = 0; i < 128; i++) asm volatile("" : "+f"(acc[i])::"memory");
#pragma unroll
    for (int i = 0; i < 64; i++) pk[i] = pack_bf16(acc[2 * i], acc[2 * i + 1]);
}
__device__ __forceinline__ void order_wait(const Ctx& c) {
    if (c.a_off) asm volatile("bar.sync 1, 256;" ::: "memory");
}
__device__ __forceinline__ void order_arrive(const Ctx& c) {
    if (!c.a_off) asm volatile("bar.arrive 1, 256;" ::: "memory");
}
template <int TB>
__device__ __forceinline__ void tile_plain(float (&acc)[128], Ctx& c) {
#pragma unroll 1
    for (int kb = 0; kb < 10; kb++) {
        const int s = c.it1 & 3;
        mbar_wait(c.sb + B_FULL1 + 8 * s, (c.it1 >> 2) & 1);
        const bool hold = kb == 10 - STAG && c.a_off;
        if (hold) { wgmma_wait<0>(); release(c, B_EMPTY1 + 8 * ((s - 1) & 3)); order_wait(c); }
        mma_s1<TB>(acc, c, s, kb == 0);
        if (kb == 9) order_arrive(c);
        wgmma_wait<1>();
        if (kb > 0 && !hold) release(c, B_EMPTY1 + 8 * ((s - 1) & 3));
        c.it1++;
    }
}
template <int I>
__device__ __forceinline__ void s1_epi_iter(float (&acc)[128], uint32_t (&pk)[64], Ctx& c, bool prev_ab) {
    const int s = c.it1 & 3;
    mbar_wait(c.sb + B_FULL1 + 8 * s, (c.it1 >> 2) & 1);
    const bool hold = I == 10 - STAG && c.a_off;
    if (hold) { wgmma_wait<0>(); release(c, B_EMPTY1 + 8 * ((s - 1) & 3)); order_wait(c); }
    mma_s1<1>(acc, c, s, I == 0);
    if (I == 9) order_arrive(c);
    wgmma_wait<1>();
    if (I > 0 && !hold) release(c, B_EMPTY1 + 8 * ((s - 1) & 3));
    c.it1++;
    epi_step<I>(pk, c, prev_ab);
}
template <int I>
__device__ __forceinline__ void s2_epi_iter(float (&acc)[80], uint32_t (&pk)[64], Ctx& c) {
    constexpr int s = I % R2_N;
    mbar_wait(c.sb + B_FULL2 + 8 * s, (I / R2_N) & 1);
    mma_s2<0>(acc, c, s, I == 0);
    wgmma_wait<1>();
    if (I > 0) release(c, B_EMPTY2 + 8 * ((I + R2_N - 1) % R2_N));
    if (I > 0 && c.on) epi_h_half<(I > 0 ? I - 1 : 0)>(pk, c);
}

__device__ __forceinline__ uint32_t out_unit(bool fin, uint32_t oh, int u) {
    if (u == 2) return R2_STAGE + oh + (fin ? 4096 : 0);
    return fin ? (2 + u) * R2_STAGE + oh : (u == 0 ? SLOTX_OFF + oh : OUT0_OFF);
}

__global__ void __cluster_dims__(2, 1, 1) __launch_bounds__(384, 1)
fused_kernel(const __grid_constant__ Maps maps, const bf16* __restrict__ x, const bf16* __restrict__ gw, bf16* __restrict__ out) {
    extern __shared__ __align__(1024) uint8_t smem_raw[];
    const uint32_t sb = smem_u32(smem_raw);
    const int warp = __shfl_sync(0xffffffffu, threadIdx.x >> 5, 0);
    const uint32_t tw = maps.tab[blockIdx.x];
    const bool first_ab = tw & 1;
    if (warp == 0) {
        const int arow = (tw >> 2) & 0x780, bc = tw >> 21;
        const CUtensorMap* ma = reinterpret_cast<const CUtensorMap*>(reinterpret_cast<const char*>(&maps.x) + (tw & 0x180));
        asm volatile("{\n.reg .pred p;\nelect.sync _|p, 0xffffffff;\n@p mbarrier.init.shared::cta.b64 [%0], %1;\n@p mbarrier.init.shared::cta.b64 [%0+8], %1;\n}" ::"r"(sb + B_FULL1), "r"(1) : "memory");
        e_expect_tma_2d(sb + B_FULL1, R1_STAGE, sb, ma, 0, arow);
        if (first_ab) {
            e_tma_2d(sb + 16384, &maps.x, 0, bc, sb + B_FULL1);
            e_tma_2d(sb + 32768, &maps.x, 0, bc + 128, sb + B_FULL1);
        }
        if (tw & 2) {
            e_tma_3d(sb + 16384, &maps.wg, 0, 0, bc, sb + B_FULL1);
            e_tma_3d(sb + 32768, &maps.wu, 0, 0, bc, sb + B_FULL1);
        }
        if (tw & 4) {
            e_tma_3d(sb + R1_STAGE + 16384, &maps.wg, 0, 64, bc, sb + B_FULL1 + 8);
            e_tma_3d(sb + R1_STAGE + 32768, &maps.wu, 0, 64, bc, sb + B_FULL1 + 8);
            e_expect_tma_2d(sb + B_FULL1 + 8, R1_STAGE, sb + R1_STAGE, &maps.x, 64, arow);
        }
        asm volatile("fence.mbarrier_init.release.cluster;" ::: "memory");
        cluster_arrive_relaxed();
    }
    const uint32_t lane = threadIdx.x & 31;
    const int a0 = (tw >> 9) & 15, b0 = (tw >> 21) >> (first_ab ? 8 : 1);
    const int rank = blockIdx.x & 1;
    const CUtensorMap* const mw = rank == 0 ? &maps.wg : &maps.wu;
    if (warp != 0) {
        if (lane == 0 && warp < 10) {
            const int cnt = 1 << ((BAR_LOG2_COUNT >> (4 * warp)) & 15);
            const uint32_t ba = sb + BAR_OFF + (warp == 9 ? 0 : 32 * warp);
            if (warp != 9) { mbar_init(ba, cnt); mbar_init(ba + 8, cnt); }
            mbar_init(ba + 16, cnt); mbar_init(ba + 24, cnt);
            asm volatile("fence.mbarrier_init.release.cluster;" ::: "memory");
        }
        __syncwarp();
        cluster_arrive_relaxed();
    }
    const int G = (tw >> 13) & 31, jm = (tw >> 18) & 3;
    const bool is_main = G < 16;
    const int nrounds = is_main ? 2 : 4;
    const int m2 = 2 * (G & 7) + rank, nb = jm, kh = (G >> 3) & 1;
    const int wid = is_main ? m2 * 8 + kh * 4 + nb : 0;
    auto h_tile = [&](int r, int& m, int& ct) {
        if (!is_main) { m = a0 + 2 * r; ct = 11; }
        else if (r == 0) { m = a0; ct = b0; }
        else { m = m2; ct = 3 + kh * 4 + nb; }
    };
    const int ab_e = a0 + ((tw >> 8) & 1) * 5, ab_s = b0;
    if (warp >= 8) {
        asm volatile("setmaxnreg.dec.sync.aligned.u32 40;");
        cluster_wait();
        if (warp == 8) {
            trap_if(sb & 1023);
            const uint64_t pol = policy_evict_first();
            constexpr int HPRE = 2;
            int it = first_ab ? 1 : HPRE;
            if (first_ab) {
                const CUtensorMap* ma = &maps.x + ((tw >> 7) & 3);
                const int arow = a0 * 128, brow = ab_s * 256 + rank * 128;
#pragma unroll 1
                for (; it < 10; it++) {
                    const int s = it & 3;
                    const uint32_t full = sb + B_FULL1 + 8 * s, dst = sb + s * R1_STAGE;
                    mbar_wait(sb + B_EMPTY1 + 8 * s, ((it >> 2) & 1) ^ 1);
                    e_expect_tma_2d(full, R1_STAGE, dst, ma, it * 64, arow);
                    e_tma_2d_mc(dst + 16384 + rank * 16384, &maps.x, it * 64, brow, full);
                }
            }
#pragma unroll 1
            for (int r = first_ab ? 1 : 0; r < nrounds; r++) {
                int m, ct;
                h_tile(r, m, ct);
#pragma unroll 1
                for (int kb = r == 0 ? HPRE : 0; kb < 10; kb++, it++) {
                    const int s = it & 3;
                    const uint32_t full = sb + B_FULL1 + 8 * s, dst = sb + s * R1_STAGE;
                    mbar_wait(sb + B_EMPTY1 + 8 * s, ((it >> 2) & 1) ^ 1);
                    e_expect_tma_2d(full, R1_STAGE, dst, &maps.x, kb * 64, m * 128);
                    e_tma_3d_mc(dst + 16384 + rank * 16384, mw, 0, kb * 64, ct * 2, full);
                }
            }
            if (is_main) {
                const CUtensorMap* mws = kh ? &maps.wsim : &maps.wsre;
                const int brow = kh * 640 + nb * 160 + rank * 80;
                const uint32_t boff = 16384 + rank * 10240;
#pragma unroll
                for (int kb = 0; kb < R2_N; kb++) {
                    const uint32_t full = sb + B_FULL2 + 8 * kb, dst = sb + kb * R2_STAGE;
                    const int kc = ((kb & 14) << 7) + ((kb & 1) << 6);
                    if (kb != 3) mbar_wait(sb + B_EMPTY1 + 8 * (kb == 4 ? 3 : kb), 0);
                    e_expect_tma_2d_hint(full, R2_STAGE, dst, mws, kc, m2 * 128, pol);
                    if (kb == 0) { mbar_wait(sb + B_DEP_AB, 0); }
                    e_tma_2d_mc(dst + boff, &maps.abT, kc, brow, full);
                }
                int s = 0, ph = 0;
#pragma unroll 1
                for (int kb = R2_N; kb < 32; kb++) {
                    const uint32_t full = sb + B_FULL2 + 8 * s, dst = sb + s * R2_STAGE;
                    const int kc = ((kb & 14) << 7) + ((kb >> 4) << 7) + ((kb & 1) << 6);
                    if (kb == 16) mbar_wait(sb + B_DEP_AB2, 0);
                    mbar_wait(sb + B_EMPTY2 + 8 * s, ph);
                    e_expect_tma_2d_hint(full, R2_STAGE, dst, mws, kc, m2 * 128, pol);
                    e_tma_2d_mc(dst + boff, &maps.abT, kc, brow, full);
                    if (++s == R2_N) { s = 0; ph ^= 1; }
                }
                mbar_wait(sb + B_DEP_H, 0);
                const int hrow = m2 * 128 + kh * 64;
#pragma unroll 1
                for (int kb = 0; kb < 9; kb++) {
                    const uint32_t full = sb + B_FULL2 + 8 * s, dst = sb + s * R2_STAGE;
                    const int kk = (kh * 9 + kb) * 64;
                    mbar_wait(sb + B_EMPTY2 + 8 * s, ph);
                    e_expect_tma_2d(full, R2_STAGE, dst, &maps.h, kk, m2 * 128);
                    e_tma_3d_mc(dst + boff, &maps.wdown, 0, kk + rank * 32, nb * 5, full);
                    if (++s == R2_N) { s = 0; ph ^= 1; }
                    if (kb == 4) {
                        mbar_wait(sb + B_FREEX, 0);
                        e_expect_tma_2d(sb + B_FULLX, R2_STAGE - 8192, sb + SLOTX_OFF + kh * 8192, &maps.h_st, 21 * 64, hrow);
                        e_tma_3d_mc(sb + SLOTX_OFF + boff, &maps.wdown, 0, 21 * 64 + rank * 32, nb * 5, sb + B_FULLX);
                    }
                }
#pragma unroll 1
                for (int j = 0; j < 5; j++) {
                    const uint32_t full = sb + B_FULL2 + 8 * s, dst = sb + s * R2_STAGE;
                    const int kk = (18 + j + (j >= 3)) * 64;
                    if (j == 3) { mbar_wait(sb + B_DEP_LATE, 0); }
                    mbar_wait(sb + B_EMPTY2 + 8 * s, ph);
                    e_expect_tma_2d(full, R2_STAGE - 8192, dst + kh * 8192, &maps.h_st, kk, hrow);
                    e_tma_3d_mc(dst + boff, &maps.wdown, 0, kk + rank * 32, nb * 5, full);
                    if (++s == R2_N) { s = 0; ph ^= 1; }
                }
                const uint32_t oh = (kh ^ 1) * 8192;
#pragma unroll
                for (int fin = 0; fin < 2; fin++) {
                    const int w = fin ? kh : kh ^ 1;
                    mbar_wait(sb + B_STGF + 16 * w, first_ab);
                    const int odd = nb & 1, orow = m2 * 128 + w * 64;
                    if (odd) e_reduce_add_3d(&maps.out, sb + out_unit(fin, oh, 2), 0, orow, nb * 5);
                    e_reduce_add_2d(&maps.out64, sb + out_unit(fin, oh, 0), nb * 160 + odd * 32, orow);
                    mbar_wait(sb + B_STGF + 16 * w + 8, first_ab);
                    e_reduce_add_2d(&maps.out64, sb + out_unit(fin, oh, 1), nb * 160 + odd * 32 + 64, orow);
                    if (!odd) e_reduce_add_3d(&maps.out, sb + out_unit(fin, oh, 2), 0, orow, nb * 5 + 4);
                }
                bulk_commit();
                bulk_wait_read0();
            }
        } else if (warp == 9) {
            if (lane < 14) prefetch_map(&maps.x + lane);
            if (lane == 0) {
                int q = 0;
                for (int r = 0; r < nrounds; r++) {
                    const bool ab = first_ab && r == 0;
                    int m, ct;
                    h_tile(r, m, ct);
                    for (int hb = 0; hb < (ab ? 2 : 1); hb++, q++) {
                        for (int p = 0; p < 4; p++) {
                            const int w = ab ? p >> 1 : p & 1, b = ab ? p & 1 : p >> 1;
                            mbar_wait(sb + B_STGF + 16 * w + 8 * b, q & 1);
                            const uint32_t src = sb + STG_OFF + b * STG_SZ + w * 8192;
                            if (ab) tma_store_2d(&maps.abT_st, src, ab_s * 256 + hb * 128 + b * 64, ab_e * 128 + w * 64);
                            else tma_store_2d(&maps.h_st, src, ct * 128 + b * 64, m * 128 + w * 64);
                            bulk_commit();
                            if (r < 3) bulk_wait_read0();
                        }
                        mbar_arrive(sb + B_STGE);
                        if (is_main && r == 1) { mbar_arrive_cluster(sb + B_FREEX, 0); mbar_arrive_cluster(sb + B_FREEX, 1); }
                        bulk_wait0();
                        flag_publish(ab ? &g_cnt[(hb ? 66 : 1) * 32] : (ct == 11 ? &g_cnt[(34 + m) * 32] : &g_cnt[(2 + m) * 32]));
                    }
                }
            }
        } else if (warp == 10) {
            if (is_main) {
                unsigned ticket = 0;
                if (lane == 0) ticket = (unsigned)(atomicAdd(&g_ticket, 1ull) >> 7);
                const unsigned epoch1 = __shfl_sync(0xffffffffu, ticket, 0) + 1;
                if (lane == 0) {
                    flag_wait(&g_cnt[1 * 32], epoch1 * 80);
                    fence_async_global();
                    mbar_arrive(sb + B_DEP_AB);
                    flag_wait(&g_cnt[66 * 32], epoch1 * 80);
                    fence_async_global();
                    mbar_arrive(sb + B_DEP_AB2);
                }
                if (lane == 0) {
                    flag_wait(&g_cnt[(2 + m2) * 32], epoch1 * 11);
                    fence_async_global();
                    mbar_arrive(sb + B_DEP_H);
                }
                __syncwarp();
                flag_wait(&g_cnt[(50 + m2) * 32], epoch1 * 8);
                fence_async_global();
                float4 gv;
                asm volatile("ld.relaxed.gpu.global.v4.f32 {%0, %1, %2, %3}, [%4];" : "=f"(gv.x), "=f"(gv.y), "=f"(gv.z), "=f"(gv.w) : "l"(g_gate + m2 * 128 + lane * 4) : "memory");
                asm volatile("st.shared.v4.f32 [%0], {%1, %2, %3, %4};" ::"r"(sb + G_OFF + lane * 16), "f"(gv.x), "f"(gv.y), "f"(gv.z), "f"(gv.w) : "memory");
                __syncwarp();
                if (lane == 0) {
                    mbar_arrive(sb + B_GRDY);
                    flag_wait(&g_cnt[(34 + m2) * 32], epoch1);
                    fence_async_global();
                    mbar_arrive(sb + B_DEP_LATE);
                }
            }
        } else if (is_main) {
            uint4* op = reinterpret_cast<uint4*>(out + (size_t)wid * 16 * D_);
            mbar_wait(sb + B_FULL1 + 24, 0);
            const uint64_t pol = policy_evict_first();
            const uint2* gw2 = reinterpret_cast<const uint2*>(gw);
            uint2 wv[5];
#pragma unroll
            for (int j = 0; j < 5; j++) wv[j] = __ldg(gw2 + j * 32 + lane);
#pragma unroll 1
            for (int i = 0; i < 8; i++) {
                const int row = wid * 16 + 2 * i;
                const uint2* xr = reinterpret_cast<const uint2*>(x + (size_t)row * D_);
                uint2 a[10];
#pragma unroll
                for (int j = 0; j < 10; j++) a[j] = __ldg(xr + j * 32 + lane);
                if (i == 0) {
                    e_prefetch_3d(mw, 0, (G & 7) * 64, (3 + kh * 4 + nb) * 2);
                    if ((G & 7) < 2) e_prefetch_3d(mw, 0, (8 + (G & 7)) * 64, (3 + kh * 4 + nb) * 2);
                }
                if (i >= 2 && i < 4) {
                    const int kp = (i - 2) * 4 + nb;
                    e_prefetch_2d_hint(kh ? &maps.wsim : &maps.wsre, ((kp & 14) << 7) + ((kp & 1) << 6), m2 * 128, pol);
                }
                if (i < 4) {
#pragma unroll
                    for (int j = 0; j < 10; j++) op[(i * 10 + j) * 32 + lane] = make_uint4(0, 0, 0, 0);
                }
                float s0 = 0.f, s1 = 0.f;
#pragma unroll
                for (int j = 0; j < 5; j++) {
                    __nv_bfloat162 p;
                    uint32_t u;
                    p = __hmul2(*reinterpret_cast<__nv_bfloat162*>(&a[j].x), *reinterpret_cast<__nv_bfloat162*>(&wv[j].x)); u = *reinterpret_cast<uint32_t*>(&p); s0 += bf_lo(u) + bf_hi(u);
                    p = __hmul2(*reinterpret_cast<__nv_bfloat162*>(&a[j].y), *reinterpret_cast<__nv_bfloat162*>(&wv[j].y)); u = *reinterpret_cast<uint32_t*>(&p); s0 += bf_lo(u) + bf_hi(u);
                    p = __hmul2(*reinterpret_cast<__nv_bfloat162*>(&a[5 + j].x), *reinterpret_cast<__nv_bfloat162*>(&wv[j].x)); u = *reinterpret_cast<uint32_t*>(&p); s1 += bf_lo(u) + bf_hi(u);
                    p = __hmul2(*reinterpret_cast<__nv_bfloat162*>(&a[5 + j].y), *reinterpret_cast<__nv_bfloat162*>(&wv[j].y)); u = *reinterpret_cast<uint32_t*>(&p); s1 += bf_lo(u) + bf_hi(u);
                }
#pragma unroll
                for (int o = 16; o > 0; o >>= 1) { s0 += __shfl_xor_sync(0xffffffffu, s0, o); s1 += __shfl_xor_sync(0xffffffffu, s1, o); }
                if (lane < 2) {
                    float z = __bfloat162float(__float2bfloat16(lane ? s1 : s0));
                    g_gate[row + lane] = __bfloat162float(__float2bfloat16(__fdividef(1.0f, 1.0f + __expf(-z))));
                }
            }
            __syncwarp();
            if (lane == 0) {
                flag_publish(&g_cnt[(50 + m2) * 32]);
            }
        }
        __syncwarp();
        if (!is_main) { cluster_arrive_relaxed(); cluster_wait(); }
    } else {
        asm volatile("setmaxnreg.inc.sync.aligned.u32 232;");
        const int wg = warp >> 2;
        Ctx c;
        c.sb = sb;
        c.a_off = wg * 8192;
        c.d16 = (sb & 0x3FFFF) >> 4;
        c.on = gridDim.x != 0;
        asm volatile("" : "+r"(c.on));
        c.lane = lane;
        asm volatile("mapa.shared::cluster.u32 %0, %1, %2;" : "=r"(c.rel) : "r"(sb), "r"(lane & 1));
        c.st_addr = sb + STG_OFF + (warp * 16 + (lane & 7) + ((lane >> 3) & 1) * 8) * 128 + (((lane >> 4) ^ (lane & 7)) << 4);
        c.it1 = 0;
        c.q = 0;
        cluster_wait();
        uint32_t pk[64];
        {
            float acc[128];
            if (first_ab) tile_plain<0>(acc, c); else tile_plain<1>(acc, c);
            finish_s1(acc, pk, c);
            bool prev_ab = first_ab;
#pragma unroll 1
            for (int r = 1; r < nrounds; r++) {
                s1_epi_iter<0>(acc, pk, c, prev_ab); s1_epi_iter<1>(acc, pk, c, prev_ab); s1_epi_iter<2>(acc, pk, c, prev_ab);
                s1_epi_iter<3>(acc, pk, c, prev_ab); s1_epi_iter<4>(acc, pk, c, prev_ab); s1_epi_iter<5>(acc, pk, c, prev_ab);
                s1_epi_iter<6>(acc, pk, c, prev_ab); s1_epi_iter<7>(acc, pk, c, prev_ab); s1_epi_iter<8>(acc, pk, c, prev_ab);
                s1_epi_iter<9>(acc, pk, c, prev_ab);
                finish_s1(acc, pk, c);
                prev_ab = false;
            }
        }
        if (!is_main) {
            epi_h<0>(pk, c); epi_h<1>(pk, c); epi_h<2>(pk, c); epi_h<3>(pk, c);
            epi_h<4>(pk, c); epi_h<5>(pk, c); epi_h<6>(pk, c); epi_h<7>(pk, c);
        } else {
            float accY[80], accF[80];
            float f0 = 0.f, f1 = 0.f;
            s2_epi_iter<0>(accY, pk, c); s2_epi_iter<1>(accY, pk, c); s2_epi_iter<2>(accY, pk, c); s2_epi_iter<3>(accY, pk, c);
            s2_epi_iter<4>(accY, pk, c); s2_epi_iter<5>(accY, pk, c); s2_epi_iter<6>(accY, pk, c); s2_epi_iter<7>(accY, pk, c);
            s2_epi_iter<8>(accY, pk, c); s2_epi_iter<9>(accY, pk, c); s2_epi_iter<10>(accY, pk, c); s2_epi_iter<11>(accY, pk, c);
            s2_epi_iter<12>(accY, pk, c); s2_epi_iter<13>(accY, pk, c); s2_epi_iter<14>(accY, pk, c); s2_epi_iter<15>(accY, pk, c);
            s2_epi_iter<16>(accY, pk, c);
            int s = 17 % R2_N, ps = 16 % R2_N, ph = (17 / R2_N) & 1;
#pragma unroll 1
            for (int kb = 17; kb < 32; kb++) {
                mbar_wait(sb + B_FULL2 + 8 * s, ph);
                mma_s2<0>(accY, c, s, false);
                wgmma_wait<1>();
                release(c, B_EMPTY2 + 8 * ps);
                ps = s;
                if (++s == R2_N) { s = 0; ph ^= 1; }
            }
            mbar_wait(sb + B_FULL2 + 8 * 2, 0);
            mma_s2<1>(accF, c, 2, true);
            wgmma_wait<1>();
            release(c, B_EMPTY2 + 8 * 1);
            {
                mbar_wait(sb + B_GRDY, 0);
                float g0, g1;
                asm volatile("ld.shared.f32 %0, [%1];" : "=f"(g0) : "r"(sb + G_OFF + 4 * (warp * 16 + (lane >> 2))));
                asm volatile("ld.shared.f32 %0, [%1];" : "=f"(g1) : "r"(sb + G_OFF + 4 * (warp * 16 + (lane >> 2) + 8)));
                f0 = __bfloat162float(__float2bfloat16(1.0f - g0)); f1 = __bfloat162float(__float2bfloat16(1.0f - g1));
                if (kh) { g0 = -g0; g1 = -g1; }
#pragma unroll
                for (int i = 0; i < 80; i++) asm volatile("" : "+f"(accY[i])::"memory");
#pragma unroll
                for (int i = 0; i < 80; i++) accY[i] *= (i & 2) ? g1 : g0;
#pragma unroll
                for (int i = 0; i < 80; i++) asm volatile("" : "+f"(accY[i])::"memory");
            }
            s = 3; ps = 2; ph = 0;
            const bool fin = wg == kh;
#pragma unroll 1
            for (int kb = 33; kb < 41; kb++) {
                mbar_wait(sb + B_FULL2 + 8 * s, ph);
                const bool hold = kb == 41 - TLAG && fin;
                if (hold) { wgmma_wait<0>(); release(c, B_EMPTY2 + 8 * ps); asm volatile("bar.sync 1, 256;" ::: "memory"); }
                mma_s2<1>(accF, c, s, false);
                if (kb == 40 && !fin) asm volatile("bar.arrive 1, 256;" ::: "memory");
                wgmma_wait<1>();
                if (!hold) release(c, B_EMPTY2 + 8 * ps);
                ps = s;
                if (++s == R2_N) { s = 0; ph ^= 1; }
            }
            if (fin) {
#pragma unroll
                for (int t = 0; t < 6; t++) {
                    const int slot = t < 3 ? t + 1 : (t == 3 ? 5 : (t == 4 ? 4 : 0));
                    mbar_wait(t == 3 ? sb + B_FULLX : sb + B_FULL2 + 8 * slot, t == 5);
                    mma_s2<1>(accF, c, slot, false);
                    if (t == 0) { wgmma_wait<1>(); release(c, B_EMPTY2); }
                }
                wgmma_wait<0>();
            } else {
                wgmma_wait<0>();
                release(c, B_EMPTY2);
                mbar_wait(sb + B_FULLX, 0);
                mbar_wait(sb + B_FULL2 + 8, 0);
            }
#pragma unroll
            for (int i = 0; i < 80; i++) asm volatile("" : "+f"(accF[i])::"memory");
            {
                const uint32_t row = (lane & 7) + ((lane >> 3) & 1) * 8;
                const uint32_t oh = (kh ^ 1) * 8192, odd = nb & 1;
                const uint32_t st32 = sb + out_unit(fin, oh, 2) + (warp & 3) * 1024 + row * 64 + (((lane >> 4) ^ ((row >> 1) & 3)) << 4);
                const uint32_t st64 = (warp & 3) * 2048 + row * 128 + (((lane >> 4) ^ (row & 7)) << 4);
                const uint32_t u0 = sb + out_unit(fin, oh, 0), u1 = sb + out_unit(fin, oh, 1);
#pragma unroll
                for (int p = 0; p < 10; p++) {
                    uint32_t o[4];
#pragma unroll
                    for (int j = 0; j < 4; j++) {
                        const int i = 8 * p + 2 * j;
                        const float f = (j & 1) ? f1 : f0;
                        o[j] = pack_bf16(fmaf(f, accF[i], accY[i]), fmaf(f, accF[i + 1], accY[i + 1]));
                    }
                    const uint32_t ae = p < 8 ? (p < 4 ? u0 : u1) + (st64 ^ ((p & 3) << 5)) : st32 ^ ((p & 1) << 5);
                    const uint32_t ao = p < 2 ? st32 ^ ((p & 1) << 5) : (p < 6 ? u0 : u1) + (st64 ^ (((p - 2) & 3) << 5));
                    stmatrix_x4(odd ? ao : ae, o[0], o[1], o[2], o[3]);
                    if (p == 5) stg_publish(c, 0);
                }
                stg_publish(c, 1);
            }
        }
        __syncwarp();
        if (!is_main) { cluster_arrive_relaxed(); cluster_wait(); }
    }
}

__global__ void fb_stage1(const bf16* x, const bf16* wdre, const bf16* wdim, const bf16* wg, const bf16* wu, const bf16* gw) {
    const int t = blockIdx.y, n = blockIdx.x * blockDim.x + threadIdx.x;
    const bf16* xr = x + (size_t)t * D_;
    if (n < 2 * D_) {
        const bf16* w = n < D_ ? wdre + (size_t)n * D_ : wdim + (size_t)(n - D_) * D_;
        float s = 0.f;
        for (int k = 0; k < D_; k++) s = fmaf(__bfloat162float(xr[k]), __bfloat162float(w[k]), s);
        g_abT[(size_t)n * S_ + t] = __float2bfloat16(s);
    } else if (n < 2 * D_ + F_) {
        const int f = n - 2 * D_;
        float g = 0.f, u = 0.f;
        for (int k = 0; k < D_; k++) {
            g = fmaf(__bfloat162float(xr[k]), __bfloat162float(wg[(size_t)k * F_ + f]), g);
            u = fmaf(__bfloat162float(xr[k]), __bfloat162float(wu[(size_t)k * F_ + f]), u);
        }
        g_H[(size_t)t * F_ + f] = __float2bfloat16(geglu(g, u));
    } else if (n == 2 * D_ + F_) {
        float s = 0.f;
        for (int k = 0; k < D_; k++) s = fmaf(__bfloat162float(xr[k]), __bfloat162float(gw[k]), s);
        g_gate[t] = 1.0f / (1.0f + __expf(-s));
    }
}
__global__ void fb_stage2(const bf16* wsre, const bf16* wsim, const bf16* wdown, bf16* out) {
    const int t = blockIdx.y, e = blockIdx.x * blockDim.x + threadIdx.x;
    float y = 0.f, f = 0.f;
    for (int k = 0; k < S_; k++)
        y += __bfloat162float(wsre[(size_t)t * S_ + k]) * __bfloat162float(g_abT[(size_t)e * S_ + k]) -
             __bfloat162float(wsim[(size_t)t * S_ + k]) * __bfloat162float(g_abT[(size_t)(D_ + e) * S_ + k]);
    for (int k = 0; k < F_; k++) f = fmaf(__bfloat162float(g_H[(size_t)t * F_ + k]), __bfloat162float(wdown[(size_t)k * D_ + e]), f);
    const float g = g_gate[t];
    out[(size_t)t * D_ + e] = __float2bfloat16(g * y + (1.0f - g) * f);
}

typedef CUresult (*EncodeFn)(CUtensorMap*, CUtensorMapDataType, cuuint32_t, void*, const cuuint64_t*, const cuuint64_t*, const cuuint32_t*,
                             const cuuint32_t*, CUtensorMapInterleave, CUtensorMapSwizzle, CUtensorMapL2promotion, CUtensorMapFloatOOBfill);

static void enc(EncodeFn fn, CUtensorMap* m, const void* ptr, int rank, cuuint64_t d0, cuuint64_t d1, cuuint64_t d2, cuuint64_t s1, cuuint64_t s2,
                cuuint32_t b0, cuuint32_t b1, cuuint32_t b2, CUtensorMapSwizzle swz) {
    cuuint64_t dims[3] = {d0, d1, d2}, strides[2] = {s1, s2};
    cuuint32_t box[3] = {b0, b1, b2}, es[3] = {1, 1, 1};
    if (fn) fn(m, CU_TENSOR_MAP_DATA_TYPE_BFLOAT16, rank, const_cast<void*>(ptr), dims, strides, box, es, CU_TENSOR_MAP_INTERLEAVE_NONE, swz,
       CU_TENSOR_MAP_L2_PROMOTION_L2_128B, CU_TENSOR_MAP_FLOAT_OOB_FILL_NONE);
}

extern "C" void kernel_launch(void* const* d_in, const int* in_sizes, int n_in, void* d_out, int out_size) {
    (void)in_sizes; (void)n_in; (void)out_size;
    const bf16* x = (const bf16*)d_in[0];
    const bf16* wsre = (const bf16*)d_in[1];
    const bf16* wsim = (const bf16*)d_in[2];
    const bf16* wdre = (const bf16*)d_in[3];
    const bf16* wdim = (const bf16*)d_in[4];
    const bf16* wg = (const bf16*)d_in[6];
    const bf16* wu = (const bf16*)d_in[7];
    const bf16* wdown = (const bf16*)d_in[8];
    const bf16* gw = (const bf16*)d_in[9];

    void* fnp = nullptr;
    cudaDriverEntryPointQueryResult qr;
    cudaGetDriverEntryPoint("cuTensorMapEncodeTiled", &fnp, cudaEnableDefault, &qr);
    EncodeFn fn = (EncodeFn)fnp;
    void *abT, *H;
    cudaGetSymbolAddress(&abT, g_abT);
    cudaGetSymbolAddress(&H, g_H);

    Maps mp = {};
    const CUtensorMapSwizzle S128 = CU_TENSOR_MAP_SWIZZLE_128B, S64 = CU_TENSOR_MAP_SWIZZLE_64B;
    enc(fn, &mp.x, x, 2, D_, S_, 1, D_ * 2, 0, 64, 128, 1, S128);
    enc(fn, &mp.wdre, wdre, 2, D_, D_, 1, D_ * 2, 0, 64, 128, 1, S128);
    enc(fn, &mp.wdim, wdim, 2, D_, D_, 1, D_ * 2, 0, 64, 128, 1, S128);
    enc(fn, &mp.wg, wg, 3, 64, D_, F_ / 64, F_ * 2, 128, 64, 64, 2, S128);
    enc(fn, &mp.wu, wu, 3, 64, D_, F_ / 64, F_ * 2, 128, 64, 64, 2, S128);
    enc(fn, &mp.wsre, wsre, 2, S_, S_, 1, S_ * 2, 0, 64, 128, 1, S128);
    enc(fn, &mp.wsim, wsim, 2, S_, S_, 1, S_ * 2, 0, 64, 128, 1, S128);
    enc(fn, &mp.abT, abT, 2, S_, 2 * D_, 1, S_ * 2, 0, 64, 80, 1, S128);
    enc(fn, &mp.abT_st, abT, 2, S_, 2 * D_, 1, S_ * 2, 0, 64, 64, 1, S128);
    enc(fn, &mp.h_st, H, 2, F_, S_, 1, F_ * 2, 0, 64, 64, 1, S128);
    enc(fn, &mp.h, H, 2, F_, S_, 1, F_ * 2, 0, 64, 128, 1, S128);
    enc(fn, &mp.wdown, wdown, 3, 32, F_, D_ / 32, D_ * 2, 64, 32, 32, 5, S64);
    enc(fn, &mp.out64, d_out, 2, D_, S_, 1, D_ * 2, 0, 64, 64, 1, S128);
    enc(fn, &mp.out, d_out, 3, 32, S_, D_ / 32, D_ * 2, 64, 32, 64, 1, S64);

    for (int b = 0; b < NCTA; b++) {
        const int c = b >> 1, t = c - 4, rank = b & 1;
        int G, j;
        if (t < 0) { G = 15; j = c; }
        else if (t < 32) { const int v = t & 7; G = v == 0 ? 14 : 2 * (v - 1); j = t >> 3; }
        else if (t < 60) { G = 2 * ((t - 32) % 7) + 1; j = (t - 32) / 7; }
        else { G = 16; j = t - 60; }
        uint32_t ab = 0, mapsel = 0, a0, b0;
        if (G < 10) {
            const int e = 2 * (G % 5) + rank;
            ab = 1; mapsel = e < 5 ? 1 : 2; a0 = e % 5; b0 = (G / 5) * 4 + j;
        } else if (G < 16) {
            const int i = (G - 10) * 4 + j;
            a0 = 2 * (i / 3) + rank; b0 = i % 3;
        } else {
            a0 = 8 * j + rank; b0 = 11;
        }
        mp.tab[b] = (ab ? 1 : 6) | (mapsel << 7) | (a0 << 9) | (G << 13) | (j << 18) | ((ab ? b0 * 256 : b0 * 2) << 21);
    }
    cudaFuncSetAttribute(fused_kernel, cudaFuncAttributeMaxDynamicSharedMemorySize, SMEM_BYTES);

    cudaLaunchConfig_t cfg = {};
    cfg.gridDim = dim3(NCTA); cfg.blockDim = dim3(384); cfg.dynamicSmemBytes = SMEM_BYTES;
    cudaLaunchAttribute at[1];
    at[0].id = cudaLaunchAttributeClusterDimension;
    at[0].val.clusterDim.x = 2; at[0].val.clusterDim.y = 1; at[0].val.clusterDim.z = 1;
    cfg.attrs = at; cfg.numAttrs = 1;
    int ncl = 0;
    if (cudaOccupancyMaxActiveClusters(&ncl, fused_kernel, &cfg) != cudaSuccess) { ncl = 0; (void)cudaGetLastError(); }
    if (fn != nullptr && ncl >= NCTA / 2) {
        fused_kernel<<<NCTA, 384, SMEM_BYTES>>>(mp, x, gw, (bf16*)d_out);
    } else {
        fb_stage1<<<dim3((2 * D_ + F_ + 1 + 127) / 128, S_), 128>>>(x, wdre, wdim, wg, wu, gw);
        fb_stage2<<<dim3(D_ / 128, S_), 128>>>(wsre, wsim, wdown, (bf16*)d_out);
    }
}
```
